```python
import torch

def _softmax(x, axis=-1):
    return torch.softmax(x, dim=axis)
def _gelu(x):
    return torch.nn.functional.gelu(x, approximate="tanh")
def _silu(x):
    return torch.nn.functional.silu(x)
def _sigmoid(x):
    return torch.sigmoid(x)
def _layernorm(x, axis=-1, eps=1e-5):
    m = x.mean(dim=axis, keepdim=True)
    v = x.var(dim=axis, keepdim=True, unbiased=False)
    return (x - m) / torch.sqrt(v + eps)
def _scatter_add(tgt, idx, src, axis=0):
    return tgt.clone().index_add_(axis, idx, src)
def _segment_sum(src, seg, n):
    out = torch.zeros((n,) + src.shape[1:], dtype=src.dtype)
    return out.index_add_(0, seg, src)
def _pad(x, pw):
    flat = tuple(v for pair in reversed(pw) for v in pair)
    return torch.nn.functional.pad(x, flat)

kernel_name = 'gated_mix__sliding_block__mixer_token_mlp__prompt'

def setup_inputs():

    _w = (lambda a: (lambda t: t.to(torch.bfloat16) if t.is_floating_point() else t)(torch.as_tensor(a)))
    def _A_setup():
        B, S, D = 1, 2048, 512
        return {
            "x": _w((lambda *s: torch.randn(*s, dtype=torch.bfloat16) * 0.05)(B, S, D)),
            "wqkv": _w((lambda *s: torch.randn(*s, dtype=torch.bfloat16) * 0.8)(D, 3 * D)),
            "wo": _w((lambda *s: torch.randn(*s, dtype=torch.bfloat16) * 0.05)(D, D)),
        }
    _A_in = _A_setup()

    def _B_setup():
        B, S, D, F = 1, 2048, 512, 1792
        return {
            "x": _w((lambda *s: torch.randn(*s, dtype=torch.bfloat16) * 0.05)(B, S, D)),
            "w1": _w((lambda *s: torch.randn(*s, dtype=torch.bfloat16) * 3.2)(S, F) * (S ** -0.5)),
            "b1": _w((lambda *s: torch.randn(*s, dtype=torch.bfloat16) * 3.2)(F) * 0.02),
            "w2": _w((lambda *s: torch.randn(*s, dtype=torch.bfloat16) * 0.1)(F, S) * (F ** -0.5)),
            "b2": _w((lambda *s: torch.randn(*s, dtype=torch.bfloat16) * 0.1)(S) * 0.02),
        }
    _B_in = _B_setup()

    return {
        "A_x": _A_in["x"],
        "A_wqkv": _A_in["wqkv"],
        "A_wo": _A_in["wo"],
        "B_x": _B_in["x"],
        "B_w1": _B_in["w1"],
        "B_b1": _B_in["b1"],
        "B_w2": _B_in["w2"],
        "B_b2": _B_in["b2"],
        "gate_w": _w((lambda *s: torch.randn(*s, dtype=torch.bfloat16) * 0.05)(512) * 16.0),
    }

def reference(A_x, A_wqkv, A_wo, B_x, B_w1, B_b1, B_w2, B_b2, gate_w):
    def _A_ref(x, wqkv, wo):
        B, S, D = x.shape
        H = 32; Dh = D // H; W = 256
        qkv = (lambda x, *d: x.permute(*d))((x @ wqkv).reshape(B, S, 3, H, Dh), 2, 0, 3, 1, 4)
        q, k, v = qkv[0], qkv[1], qkv[2]
        scores = torch.einsum("bhqd,bhkd->bhqk", q, k) * (Dh ** -0.5)
        idx = torch.arange(S)
        mask = (idx[:, None] - idx[None, :] >= 0) & (idx[:, None] - idx[None, :] < W)
        scores = torch.where(mask[None, None], scores, -1e9)
        p = _softmax(scores, axis=-1)
        o = torch.einsum("bhqk,bhkd->bhqd", p, v)
        return (lambda x, *d: x.permute(*d))(o, 0, 2, 1, 3).reshape(B, S, D) @ wo

    def _B_ref(x, w1, b1, w2, b2):
        B, S, D = x.shape
        h = _layernorm(x, axis=-1)
        u = torch.einsum("bsd,sf->bdf", h, w1) + b1
        u = _gelu(u)
        y = torch.einsum("bdf,fs->bds", u, w2) + b2
        return (lambda x, *d: x.permute(*d))(y, 0, 2, 1)

    x = A_x
    g = _sigmoid((x * gate_w).sum(-1, keepdims=True))
    a = _A_ref(x, A_wqkv, A_wo)
    b = _B_ref(x, B_w1, B_b1, B_w2, B_b2)
    return g * a + (1 - g) * b
```

```cpp
#include <cuda_runtime.h>
#include <cuda_bf16.h>
#include <cuda.h>
#include <stdint.h>

#define NFIRST 2
#define D0 1800
#define DS 600
#define DL 1400
#define NA 8
#define DL2 0
#define LREV 0
#define HOLDJ 1
namespace {

constexpr int S_LEN = 2048, D_DIM = 512, F_DIM = 1792;
constexpr int NCTA = 128;
constexpr int NQ = 4, Q_BYTES = 40960;
constexpr int NG = 5, G_BYTES = 32768;
constexpr int NVAL = 4;
constexpr int KV_SLOT = 24576;
constexpr int OFF_KV = NQ * Q_BYTES;
constexpr int OFF_X = OFF_KV + 2 * KV_SLOT;
constexpr int OFF_BAR = OFF_X + 16384;
constexpr int SMEM_BYTES = OFF_BAR + 640 + 1024;
constexpr int POLL_LIMIT = 200000;

__device__ __align__(1024) __nv_bfloat16 g_h[2 * S_LEN * D_DIM];
__device__ __align__(1024) __nv_bfloat16 g_o[S_LEN * D_DIM];
__device__ __align__(1024) __nv_bfloat16 g_ut[2 * F_DIM * D_DIM];
__device__ __align__(1024) __nv_bfloat16 g_wo[D_DIM * D_DIM];
__device__ __align__(1024) unsigned char g_kv[32 * 256 * 512];
__device__ __align__(128) float g_gate[S_LEN];
__device__ __align__(1024) unsigned char g_llkv[2 * NCTA * 16384];
__device__ __align__(1024) unsigned char g_llo[2 * 64 * 8192];
__device__ __align__(128) unsigned g_epoch[32];
constexpr int FL_KV = 0, FL_O = 128, FL_U = 160, FL_LN = 188, FL_AUX = 220, FL_CLAIM = 236, FL_DONE = 252;
constexpr int FS = 32, NFLAGS = 253;
__device__ __align__(128) unsigned g_flags[NFLAGS * FS];

#define TL(i)
#define TL1(i)
#define TLA(i)

struct Params {
    const __nv_bfloat16* x;
    const __nv_bfloat16* gw;
    const __nv_bfloat16* wo;
    const __nv_bfloat16* wqkv;
    const __nv_bfloat16* w1;
    const __nv_bfloat16* w2;
    const __nv_bfloat16* b1;
    const __nv_bfloat16* b2;
    __nv_bfloat16* out;
    __nv_bfloat16* h;
    __nv_bfloat16* ut;
    __nv_bfloat16* wos;
    unsigned char* kv;
    float* gate;
    unsigned* flags;
    unsigned char* llkv;
    unsigned char* llo;
    unsigned* epoch;
    long long* tl;
    unsigned char bucket[72];
};

__device__ __forceinline__ uint32_t smem_u32(const void* p) { return (uint32_t)__cvta_generic_to_shared(p); }
__device__ __forceinline__ void mbar_init(uint32_t bar, int cnt) {
    asm volatile("mbarrier.init.shared::cta.b64 [%0], %1;" ::"r"(bar), "r"(cnt) : "memory");
}
__device__ __forceinline__ void mbar_expect_tx(uint32_t bar, uint32_t bytes) {
    asm volatile("mbarrier.arrive.expect_tx.shared::cta.b64 _, [%0], %1;" ::"r"(bar), "r"(bytes) : "memory");
}
__device__ __forceinline__ void mbar_arrive(uint32_t bar) {
    asm volatile("mbarrier.arrive.shared::cta.b64 _, [%0];" ::"r"(bar) : "memory");
}
__device__ __forceinline__ void mbar_arrive_n(uint32_t bar, uint32_t n) {
    asm volatile("mbarrier.arrive.shared::cta.b64 _, [%0], %1;" ::"r"(bar), "r"(n) : "memory");
}
__device__ __forceinline__ void mbar_arrive_remote(uint32_t remote_bar) {
    asm volatile("mbarrier.arrive.shared::cluster.b64 _, [%0];" ::"r"(remote_bar) : "memory");
}
__device__ __forceinline__ uint32_t clock32() { uint32_t t; asm volatile("mov.u32 %0, %%clock;" : "=r"(t)); return t; }
__device__ __forceinline__ void mbar_wait(uint32_t bar, uint32_t parity) {
    asm volatile("{\n.reg .pred p;\n.reg .b32 n;\nmov.b32 n, 0;\nW_%=:\n"
                 "mbarrier.try_wait.parity.shared::cta.b64 p, [%0], %1;\n"
                 "add.u32 n, n, 1;\nsetp.gt.or.u32 p, n, 400000, p;\n@!p bra W_%=;\n}" ::"r"(bar), "r"(parity) : "memory");
}
__device__ __forceinline__ void mbar_wait_cluster(uint32_t bar, uint32_t parity) {
    asm volatile("{\n.reg .pred p;\n.reg .b32 n;\nmov.b32 n, 0;\nW_%=:\n"
                 "mbarrier.try_wait.parity.acquire.cluster.shared::cta.b64 p, [%0], %1;\n"
                 "add.u32 n, n, 1;\nsetp.gt.or.u32 p, n, 400000, p;\n@!p bra W_%=;\n}" ::"r"(bar), "r"(parity) : "memory");
}
__device__ __forceinline__ uint32_t mapa(uint32_t addr, uint32_t cta) {
    uint32_t r;
    asm("mapa.shared::cluster.u32 %0, %1, %2;" : "=r"(r) : "r"(addr), "r"(cta));
    return r;
}
__device__ __forceinline__ void load_stage(uint32_t bar, uint32_t bytes, uint32_t d0, const CUtensorMap* m0, int x0, int y0, int z0,
                                           uint32_t d1, const CUtensorMap* m1, int x1, int y1, int z1) {
    asm volatile("{\n.reg .pred p;\nelect.sync _|p, 0xffffffff;\n"
                 "@p mbarrier.arrive.expect_tx.shared::cta.b64 _, [%0], %1;\n"
                 "@p cp.async.bulk.tensor.3d.shared::cluster.global.mbarrier::complete_tx::bytes [%2], [%3, {%4, %5, %6}], [%0];\n"
                 "@p cp.async.bulk.tensor.3d.shared::cluster.global.mbarrier::complete_tx::bytes [%7], [%8, {%9, %10, %11}], [%0];\n}"
                 ::"r"(bar), "r"(bytes), "r"(d0), "l"(m0), "r"(x0), "r"(y0), "r"(z0), "r"(d1), "l"(m1), "r"(x1), "r"(y1), "r"(z1) : "memory");
}
__device__ __forceinline__ void load_g(uint32_t bar, uint32_t bytes, uint32_t st, const CUtensorMap* ma, int za, const CUtensorMap* mb, int zb,
                                       int y, int g, int gb) {
    asm volatile("{\n.reg .pred p;\nelect.sync _|p, 0xffffffff;\n"
                 "@p mbarrier.arrive.expect_tx.shared::cta.b64 _, [%0], %1;\n"
                 "@p cp.async.bulk.tensor.4d.shared::cluster.global.mbarrier::complete_tx::bytes [%2], [%3, {%9, %7, %8, %4}], [%0];\n"
                 "@p cp.async.bulk.tensor.4d.shared::cluster.global.mbarrier::complete_tx::bytes [%10], [%5, {%9, %7, %11, %6}], [%0];\n}"
                 ::"r"(bar), "r"(bytes), "r"(st), "l"(ma), "r"(za), "l"(mb), "r"(zb), "r"(y), "r"(g), "r"(0), "r"(st + 16384), "r"(gb) : "memory");
}
__device__ __forceinline__ void load_a(uint32_t bar, uint32_t bytes, uint32_t d0, const CUtensorMap* m0, int y, int g, int z) {
    asm volatile("{\n.reg .pred p;\nelect.sync _|p, 0xffffffff;\n"
                 "@p mbarrier.arrive.expect_tx.shared::cta.b64 _, [%0], %1;\n"
                 "@p cp.async.bulk.tensor.4d.shared::cluster.global.mbarrier::complete_tx::bytes [%2], [%3, {%7, %4, %5, %6}], [%0];\n}"
                 ::"r"(bar), "r"(bytes), "r"(d0), "l"(m0), "r"(y), "r"(g), "r"(z), "r"(0) : "memory");
}
__device__ __forceinline__ void load_b(uint32_t bar, uint32_t d0, const CUtensorMap* m0, int y, int g, int z) {
    asm volatile("{\n.reg .pred p;\nelect.sync _|p, 0xffffffff;\n"
                 "@p cp.async.bulk.tensor.4d.shared::cluster.global.mbarrier::complete_tx::bytes [%1], [%2, {%6, %3, %4, %5}], [%0];\n}"
                 ::"r"(bar), "r"(d0), "l"(m0), "r"(y), "r"(g), "r"(z), "r"(0) : "memory");
}
__device__ __forceinline__ void tma4d_store(const CUtensorMap* m, uint32_t src, int y, int g, int z) {
    asm volatile("cp.async.bulk.tensor.4d.global.shared::cta.bulk_group [%0, {%5, %2, %3, %4}], [%1];"
                 ::"l"(m), "r"(src), "r"(y), "r"(g), "r"(z), "r"(0) : "memory");
}
__device__ __forceinline__ void bulk_g2s(uint32_t dst, const void* src, uint32_t bytes, uint32_t bar) {
    asm volatile("cp.async.bulk.shared::cluster.global.mbarrier::complete_tx::bytes [%0], [%1], %2, [%3];"
                 ::"r"(dst), "l"(src), "r"(bytes), "r"(bar) : "memory");
}
__device__ __forceinline__ void prefetch_tmap(const CUtensorMap* m) {
    asm volatile("prefetch.tensormap [%0];" ::"l"(m) : "memory");
}
__device__ __forceinline__ void wg_bar(int id) { asm volatile("bar.sync %0, 128;" ::"r"(id) : "memory"); }
__device__ __forceinline__ void bulk_done() {
    asm volatile("cp.async.bulk.commit_group;" ::: "memory");
    asm volatile("cp.async.bulk.wait_group 0;" ::: "memory");
}
__device__ __forceinline__ void release_add(unsigned* p, unsigned n) {
    asm volatile("red.release.gpu.global.add.u32 [%0], %1;" ::"l"(p), "r"(n) : "memory");
}
__device__ __forceinline__ void fence_async_smem() { asm volatile("fence.proxy.async.shared::cta;" ::: "memory"); }
__device__ __forceinline__ void bulk_s2g(void* dst, uint32_t src, uint32_t bytes) {
    asm volatile("cp.async.bulk.global.shared::cta.bulk_group [%0], [%1], %2;" ::"l"(dst), "r"(src), "r"(bytes) : "memory");
}
__device__ __forceinline__ void tma3d_store(const CUtensorMap* m, uint32_t src, int c0, int c1, int c2) {
    asm volatile("cp.async.bulk.tensor.3d.global.shared::cta.bulk_group [%0, {%2, %3, %4}], [%1];"
                 ::"l"(m), "r"(src), "r"(c0), "r"(c1), "r"(c2) : "memory");
}
__device__ __forceinline__ void sts128(uint32_t a, uint32_t x, uint32_t y, uint32_t z, uint32_t w) {
    asm volatile("st.shared.v4.u32 [%0], {%1,%2,%3,%4};" ::"r"(a), "r"(x), "r"(y), "r"(z), "r"(w) : "memory");
}
__device__ __forceinline__ void sts32(uint32_t a, uint32_t x) { asm volatile("st.shared.u32 [%0], %1;" ::"r"(a), "r"(x) : "memory"); }
__device__ __forceinline__ void stmatrix4(uint32_t a, uint32_t x, uint32_t y, uint32_t z, uint32_t w) {
    asm volatile("stmatrix.sync.aligned.m8n8.x4.shared.b16 [%0], {%1,%2,%3,%4};" ::"r"(a), "r"(x), "r"(y), "r"(z), "r"(w) : "memory");
}
__device__ __forceinline__ void stmatrix4t(uint32_t a, uint32_t x, uint32_t y, uint32_t z, uint32_t w) {
    asm volatile("stmatrix.sync.aligned.m8n8.x4.trans.shared.b16 [%0], {%1,%2,%3,%4};" ::"r"(a), "r"(x), "r"(y), "r"(z), "r"(w) : "memory");
}
__device__ __forceinline__ unsigned flag_poll(const unsigned* p) {
    unsigned v;
    asm volatile("ld.relaxed.gpu.global.u32 %0, [%1];" : "=r"(v) : "l"(p) : "memory");
    return v;
}
__device__ __forceinline__ void flag_wait(const unsigned* p, unsigned target, unsigned v = 0) {
#pragma unroll 1
    for (int it = 0; v < target && it < POLL_LIMIT; it++) v = flag_poll(p);
    asm volatile("fence.acquire.gpu;" ::: "memory");
    asm volatile("fence.proxy.async.global;" ::: "memory");
}
__device__ __forceinline__ void flags_wait(const unsigned* p, unsigned target, unsigned v, bool act) {
    if (!act) v = target;
#pragma unroll 1
    for (int it = 0; __any_sync(0xffffffffu, v < target) && it < POLL_LIMIT; it++)
        if (v < target) v = flag_poll(p);
    __syncwarp();
    asm volatile("fence.acquire.gpu;" ::: "memory");
    asm volatile("fence.proxy.async.global;" ::: "memory");
}
__device__ __forceinline__ uint4 lds128(uint32_t a) {
    uint4 v;
    asm volatile("ld.shared.v4.u32 {%0,%1,%2,%3}, [%4];" : "=r"(v.x), "=r"(v.y), "=r"(v.z), "=r"(v.w) : "r"(a) : "memory");
    return v;
}
__device__ __forceinline__ uint32_t nz(uint32_t x) { return x == 0 ? 0x8000u : x; }
__device__ __forceinline__ bool has_zero(const uint4& v) { return v.x == 0 || v.y == 0 || v.z == 0 || v.w == 0; }
__device__ __forceinline__ void ll_mark(uint32_t a) {
    const uint4 v = lds128(a);
    if (has_zero(v)) sts128(a, nz(v.x), nz(v.y), nz(v.z), nz(v.w));
}
__device__ __forceinline__ void ll_repair(uint32_t a, const void* g) {
    uint4 v = lds128(a);
    if (!has_zero(v)) return;
    int it = 0;
    do {
        asm volatile("ld.relaxed.gpu.global.v4.u32 {%0,%1,%2,%3}, [%4];" : "=r"(v.x), "=r"(v.y), "=r"(v.z), "=r"(v.w) : "l"(g) : "memory");
    } while (has_zero(v) && ++it < POLL_LIMIT);
    sts128(a, v.x, v.y, v.z, v.w);
    fence_async_smem();
}
template <int N>
__device__ __forceinline__ bool ll_probe(uint32_t a, int lane) {
    uint32_t bad = 0;
#pragma unroll
    for (int i = 0; i < N; i++) {
        uint32_t v;
        asm volatile("ld.shared.u32 %0, [%1];" : "=r"(v) : "r"(a + i * 1024 + lane * 32 + (lane >> 2) * 4) : "memory");
        bad |= v == 0;
    }
    return __any_sync(0xffffffffu, bad);
}
template <int N>
__device__ __forceinline__ void ll_check(uint32_t a, const unsigned char* g, int lane) {
    if (ll_probe<N>(a, lane)) {
#pragma unroll 1
        for (int i = 0; i < 2 * N; i++) { ll_repair(a + i * 512 + lane * 16, g + i * 512 + lane * 16); __syncwarp(); }
    }
}
template <class F>
__device__ __forceinline__ void ll_check_tile(uint32_t st, F src, int gstride, int w, int lane) {
    if (ll_probe<4>(st + w * 4096, lane)) {
        const unsigned char* g = src();
#pragma unroll 1
        for (int i = 0; i < 8; i++) {
            const int r = (w & 1) * 32 + i * 4 + (lane >> 3);
            ll_repair(st + w * 4096 + i * 512 + lane * 16, g + (r >> 3) * gstride + (r & 7) * 1024 + (w >> 1) * 128 + (((lane ^ r) & 7) << 4));
            __syncwarp();
        }
    }
    wg_bar(1);
}
__device__ __forceinline__ void sts128_marked(uint32_t a, uint32_t x, uint32_t y, uint32_t z, uint32_t w) { sts128(a, nz(x), nz(y), nz(z), nz(w)); }
__device__ __forceinline__ unsigned atom_inc(unsigned* p) {
    unsigned v;
    asm volatile("atom.relaxed.gpu.global.add.u32 %0, [%1], 1;" : "=r"(v) : "l"(p) : "memory");
    return v;
}
__device__ __forceinline__ void hint_add(unsigned* p) { asm volatile("red.relaxed.gpu.global.add.u32 [%0], 1;" ::"l"(p) : "memory"); }
__device__ __forceinline__ uint32_t pack_bf16(float lo, float hi) {
    uint32_t r;
    asm("cvt.rn.bf16x2.f32 %0, %1, %2;" : "=r"(r) : "f"(hi), "f"(lo));
    return r;
}
__device__ __forceinline__ float bf_lo(uint32_t v) { return __uint_as_float(v << 16); }
__device__ __forceinline__ float bf_hi(uint32_t v) { return __uint_as_float(v & 0xFFFF0000u); }
__device__ __forceinline__ float ex2(float x) {
    float r;
    asm("ex2.approx.ftz.f32 %0, %1;" : "=f"(r) : "f"(x));
    return r;
}
__device__ __forceinline__ float tanh_fast(float x) {
    float r;
    asm("tanh.approx.f32 %0, %1;" : "=f"(r) : "f"(x));
    return r;
}
__device__ __forceinline__ void wgmma_fence() { asm volatile("wgmma.fence.sync.aligned;" ::: "memory"); }
__device__ __forceinline__ void wgmma_commit() { asm volatile("wgmma.commit_group.sync.aligned;" ::: "memory"); }
template <int N> __device__ __forceinline__ void wgmma_wait() { asm volatile("wgmma.wait_group.sync.aligned %0;" ::"n"(N) : "memory"); }
template <int N> __device__ __forceinline__ void fence_regs(float (&a)[N]) {
#pragma unroll
    for (int i = 0; i < N; i++) asm volatile("" : "+f"(a[i])::"memory");
}
template <int N> __device__ __forceinline__ void zero_regs(float (&a)[N]) {
#pragma unroll
    for (int i = 0; i < N; i++) a[i] = 0.f;
}
__device__ __forceinline__ uint64_t make_desc(uint32_t addr) {
    return (uint64_t)((addr & 0x3FFFF) >> 4) | ((uint64_t)(8192 >> 4) << 16) | ((uint64_t)(1024 >> 4) << 32) | (1ull << 62);
}

__device__ __forceinline__ uint64_t desc_k(uint32_t a16) { return (uint64_t)(a16 | (8u << 16)) | ((uint64_t)32 << 32); }
__device__ __forceinline__ uint64_t desc_v(uint32_t a16) { return (uint64_t)((a16 + 16) | (32u << 16)) | ((uint64_t)8 << 32); }
__device__ __forceinline__ uint64_t desc_q(uint32_t a16) { return (uint64_t)(a16 | (8u << 16)) | ((uint64_t)16 << 32); }

template <int TA, int TB> __device__ __forceinline__ void wgmma_m64n16k16_rs(float (&d)[8], uint32_t a0, uint32_t a1, uint32_t a2, uint32_t a3, uint64_t db) {
    asm volatile("wgmma.mma_async.sync.aligned.m64n16k16.f32.bf16.bf16 {%0, %1, %2, %3, %4, %5, %6, %7}, {%8,%9,%10,%11}, %12, 1, 1, 1, %13;"
        : "+f"(d[0]), "+f"(d[1]), "+f"(d[2]), "+f"(d[3]), "+f"(d[4]), "+f"(d[5]), "+f"(d[6]), "+f"(d[7])
        : "r"(a0), "r"(a1), "r"(a2), "r"(a3), "l"(db), "n"(TB));
}
template <int TA, int TB> __device__ __forceinline__ void wgmma_m64n16k16_rs0(float (&d)[8], uint32_t a0, uint32_t a1, uint32_t a2, uint32_t a3, uint64_t db) {
    asm volatile("wgmma.mma_async.sync.aligned.m64n16k16.f32.bf16.bf16 {%0, %1, %2, %3, %4, %5, %6, %7}, {%8,%9,%10,%11}, %12, 0, 1, 1, %13;"
        : "=f"(d[0]), "=f"(d[1]), "=f"(d[2]), "=f"(d[3]), "=f"(d[4]), "=f"(d[5]), "=f"(d[6]), "=f"(d[7])
        : "r"(a0), "r"(a1), "r"(a2), "r"(a3), "l"(db), "n"(TB));
}
template <int TA, int TB> __device__ __forceinline__ void wgmma_m64n64k16_ss0(float (&d)[32], uint64_t da, uint64_t db) {
    asm volatile("wgmma.mma_async.sync.aligned.m64n64k16.f32.bf16.bf16 {%0, %1, %2, %3, %4, %5, %6, %7, %8, %9, %10, %11, %12, %13, %14, %15, %16, %17, %18, %19, %20, %21, %22, %23, %24, %25, %26, %27, %28, %29, %30, %31}, %32, %33, 0, 1, 1, %34, %35;"
        : "=f"(d[0]), "=f"(d[1]), "=f"(d[2]), "=f"(d[3]), "=f"(d[4]), "=f"(d[5]), "=f"(d[6]), "=f"(d[7]), "=f"(d[8]), "=f"(d[9]), "=f"(d[10]), "=f"(d[11]), "=f"(d[12]), "=f"(d[13]), "=f"(d[14]), "=f"(d[15]), "=f"(d[16]), "=f"(d[17]), "=f"(d[18]), "=f"(d[19]), "=f"(d[20]), "=f"(d[21]), "=f"(d[22]), "=f"(d[23]), "=f"(d[24]), "=f"(d[25]), "=f"(d[26]), "=f"(d[27]), "=f"(d[28]), "=f"(d[29]), "=f"(d[30]), "=f"(d[31])
        : "l"(da), "l"(db), "n"(TA), "n"(TB));
}
template <int TA, int TB> __device__ __forceinline__ void wgmma_m64n128k16_ss(float (&d)[64], uint64_t da, uint64_t db) {
    asm volatile("wgmma.mma_async.sync.aligned.m64n128k16.f32.bf16.bf16 {%0, %1, %2, %3, %4, %5, %6, %7, %8, %9, %10, %11, %12, %13, %14, %15, %16, %17, %18, %19, %20, %21, %22, %23, %24, %25, %26, %27, %28, %29, %30, %31, %32, %33, %34, %35, %36, %37, %38, %39, %40, %41, %42, %43, %44, %45, %46, %47, %48, %49, %50, %51, %52, %53, %54, %55, %56, %57, %58, %59, %60, %61, %62, %63}, %64, %65, 1, 1, 1, %66, %67;"
        : "+f"(d[0]), "+f"(d[1]), "+f"(d[2]), "+f"(d[3]), "+f"(d[4]), "+f"(d[5]), "+f"(d[6]), "+f"(d[7]), "+f"(d[8]), "+f"(d[9]), "+f"(d[10]), "+f"(d[11]), "+f"(d[12]), "+f"(d[13]), "+f"(d[14]), "+f"(d[15]), "+f"(d[16]), "+f"(d[17]), "+f"(d[18]), "+f"(d[19]), "+f"(d[20]), "+f"(d[21]), "+f"(d[22]), "+f"(d[23]), "+f"(d[24]), "+f"(d[25]), "+f"(d[26]), "+f"(d[27]), "+f"(d[28]), "+f"(d[29]), "+f"(d[30]), "+f"(d[31]), "+f"(d[32]), "+f"(d[33]), "+f"(d[34]), "+f"(d[35]), "+f"(d[36]), "+f"(d[37]), "+f"(d[38]), "+f"(d[39]), "+f"(d[40]), "+f"(d[41]), "+f"(d[42]), "+f"(d[43]), "+f"(d[44]), "+f"(d[45]), "+f"(d[46]), "+f"(d[47]), "+f"(d[48]), "+f"(d[49]), "+f"(d[50]), "+f"(d[51]), "+f"(d[52]), "+f"(d[53]), "+f"(d[54]), "+f"(d[55]), "+f"(d[56]), "+f"(d[57]), "+f"(d[58]), "+f"(d[59]), "+f"(d[60]), "+f"(d[61]), "+f"(d[62]), "+f"(d[63])
        : "l"(da), "l"(db), "n"(TA), "n"(TB));
}
template <int TA, int TB> __device__ __forceinline__ void wgmma_m64n192k16_ss(float (&d)[96], uint64_t da, uint64_t db) {
    asm volatile("wgmma.mma_async.sync.aligned.m64n192k16.f32.bf16.bf16 {%0, %1, %2, %3, %4, %5, %6, %7, %8, %9, %10, %11, %12, %13, %14, %15, %16, %17, %18, %19, %20, %21, %22, %23, %24, %25, %26, %27, %28, %29, %30, %31, %32, %33, %34, %35, %36, %37, %38, %39, %40, %41, %42, %43, %44, %45, %46, %47, %48, %49, %50, %51, %52, %53, %54, %55, %56, %57, %58, %59, %60, %61, %62, %63, %64, %65, %66, %67, %68, %69, %70, %71, %72, %73, %74, %75, %76, %77, %78, %79, %80, %81, %82, %83, %84, %85, %86, %87, %88, %89, %90, %91, %92, %93, %94, %95}, %96, %97, 1, 1, 1, %98, %99;"
        : "+f"(d[0]), "+f"(d[1]), "+f"(d[2]), "+f"(d[3]), "+f"(d[4]), "+f"(d[5]), "+f"(d[6]), "+f"(d[7]), "+f"(d[8]), "+f"(d[9]), "+f"(d[10]), "+f"(d[11]), "+f"(d[12]), "+f"(d[13]), "+f"(d[14]), "+f"(d[15]), "+f"(d[16]), "+f"(d[17]), "+f"(d[18]), "+f"(d[19]), "+f"(d[20]), "+f"(d[21]), "+f"(d[22]), "+f"(d[23]), "+f"(d[24]), "+f"(d[25]), "+f"(d[26]), "+f"(d[27]), "+f"(d[28]), "+f"(d[29]), "+f"(d[30]), "+f"(d[31]), "+f"(d[32]), "+f"(d[33]), "+f"(d[34]), "+f"(d[35]), "+f"(d[36]), "+f"(d[37]), "+f"(d[38]), "+f"(d[39]), "+f"(d[40]), "+f"(d[41]), "+f"(d[42]), "+f"(d[43]), "+f"(d[44]), "+f"(d[45]), "+f"(d[46]), "+f"(d[47]), "+f"(d[48]), "+f"(d[49]), "+f"(d[50]), "+f"(d[51]), "+f"(d[52]), "+f"(d[53]), "+f"(d[54]), "+f"(d[55]), "+f"(d[56]), "+f"(d[57]), "+f"(d[58]), "+f"(d[59]), "+f"(d[60]), "+f"(d[61]), "+f"(d[62]), "+f"(d[63]), "+f"(d[64]), "+f"(d[65]), "+f"(d[66]), "+f"(d[67]), "+f"(d[68]), "+f"(d[69]), "+f"(d[70]), "+f"(d[71]), "+f"(d[72]), "+f"(d[73]), "+f"(d[74]), "+f"(d[75]), "+f"(d[76]), "+f"(d[77]), "+f"(d[78]), "+f"(d[79]), "+f"(d[80]), "+f"(d[81]), "+f"(d[82]), "+f"(d[83]), "+f"(d[84]), "+f"(d[85]), "+f"(d[86]), "+f"(d[87]), "+f"(d[88]), "+f"(d[89]), "+f"(d[90]), "+f"(d[91]), "+f"(d[92]), "+f"(d[93]), "+f"(d[94]), "+f"(d[95])
        : "l"(da), "l"(db), "n"(TA), "n"(TB));
}

struct Ring { int s; uint32_t ph; };
__device__ __forceinline__ uint32_t gslot(uint32_t sbase, uint32_t pos) { return sbase + (pos == 0 ? 4 : pos - 1) * G_BYTES; }
__device__ __forceinline__ void ring_adv(Ring& r) { if (++r.s == NG) { r.s = 0; r.ph ^= 1; } }

__device__ __forceinline__ void mma4(float (&acc)[64], uint64_t da, uint64_t db) {
#pragma unroll
    for (int kk = 0; kk < 4; kk++) wgmma_m64n128k16_ss<1, 1>(acc, da + kk * 128, db + kk * 128);
}
__device__ __forceinline__ void send1(const float (&v)[64], int i, uint32_t rdst, uint32_t rbar) {
    const float* t = &v[(i & 3) * 16 + (i >> 2) * 2];
    asm volatile("st.async.weak.shared::cluster.mbarrier::complete_tx::bytes.v4.b32 [%0], {%1,%2,%3,%4}, [%5];"
                 ::"r"(rdst + i * 2048), "r"(pack_bf16(t[0], t[1])), "r"(pack_bf16(t[4], t[5])), "r"(pack_bf16(t[8], t[9])),
                 "r"(pack_bf16(t[12], t[13])), "r"(rbar) : "memory");
}
__device__ __forceinline__ void add1(float (&v)[64], int i, const uint4& x) {
    float* t = &v[(i & 3) * 16 + (i >> 2) * 2];
    t[0] += bf_lo(x.x); t[1] += bf_hi(x.x); t[4] += bf_lo(x.y); t[5] += bf_hi(x.y);
    t[8] += bf_lo(x.z); t[9] += bf_hi(x.z); t[12] += bf_lo(x.w); t[13] += bf_hi(x.w);
}

__device__ __forceinline__ float gelu_tanh(float u) {
    float inner = u * fmaf(0.044715f * 0.7978845608028654f, u * u, 0.7978845608028654f);
    return fmaf(u, tanh_fast(inner), u);
}

__device__ __forceinline__ void local_max(const float (&s)[32], float& m0, float& m1) {
    float a0 = fmaxf(s[0], s[1]), a1 = fmaxf(s[2], s[3]), b0 = fmaxf(s[4], s[5]), b1 = fmaxf(s[6], s[7]);
#pragma unroll
    for (int j = 2; j < 8; j += 2) {
        a0 = fmaxf(a0, fmaxf(s[4 * j], s[4 * j + 1])); a1 = fmaxf(a1, fmaxf(s[4 * j + 2], s[4 * j + 3]));
        b0 = fmaxf(b0, fmaxf(s[4 * j + 4], s[4 * j + 5])); b1 = fmaxf(b1, fmaxf(s[4 * j + 6], s[4 * j + 7]));
    }
    m0 = fmaxf(a0, b0); m1 = fmaxf(a1, b1);
}
__device__ __forceinline__ void quad_max(float& m0, float& m1) {
    m0 = fmaxf(m0, __shfl_xor_sync(0xffffffffu, m0, 1)); m1 = fmaxf(m1, __shfl_xor_sync(0xffffffffu, m1, 1));
    m0 = fmaxf(m0, __shfl_xor_sync(0xffffffffu, m0, 2)); m1 = fmaxf(m1, __shfl_xor_sync(0xffffffffu, m1, 2));
}
constexpr float SM_C = 0.25f * 1.4426950408889634f;
__device__ __forceinline__ void exp_pack(const float (&s)[32], uint32_t (&p)[16], float m0, float m1, float& l0, float& l1, bool valid) {
    if (!valid) { m0 = INFINITY; m1 = INFINITY; }
#pragma unroll
    for (int j = 0; j < 8; j++) {
        const float e0 = ex2(s[4 * j] - m0), e1 = ex2(s[4 * j + 1] - m0), e2 = ex2(s[4 * j + 2] - m1), e3 = ex2(s[4 * j + 3] - m1);
        l0 += e0 + e1;
        l1 += e2 + e3;
        p[2 * j] = pack_bf16(e0, e1);
        p[2 * j + 1] = pack_bf16(e2, e3);
    }
}
__device__ __forceinline__ void pin(uint32_t& p, float l0, float l1) { p ^= (__float_as_uint(l0) | __float_as_uint(l1)) >> 31; }
template <bool FIRST>
__device__ __forceinline__ void pv_chunk(float (&o)[8], const uint32_t (&p)[16], uint32_t a16) {
    const uint64_t dv = desc_v(a16);
    if (FIRST) wgmma_m64n16k16_rs0<0, 1>(o, p[0], p[1], p[2], p[3], dv);
    else wgmma_m64n16k16_rs<0, 1>(o, p[0], p[1], p[2], p[3], dv);
#pragma unroll
    for (int b = 1; b < 4; b++) wgmma_m64n16k16_rs<0, 1>(o, p[4 * b], p[4 * b + 1], p[4 * b + 2], p[4 * b + 3], dv + b * 64);
}
__device__ __forceinline__ void scale_o(float (&o)[8], float a0, float a1) {
    o[0] *= a0; o[1] *= a0; o[4] *= a0; o[5] *= a0;
    o[2] *= a1; o[3] *= a1; o[6] *= a1; o[7] *= a1;
}

__device__ __forceinline__ void attn_safe(uint32_t q16, uint32_t k16, uint32_t z16, int gc0, int thr, float g0, float g1, uint32_t oad,
                                          int barid) {
    const uint32_t c0 = gc0 >= 0 ? k16 : z16, c1 = gc0 + 1 >= 0 ? k16 + 256 : z16, c2 = gc0 + 2 >= 0 ? k16 + 512 : z16,
                   c3 = gc0 + 3 >= 0 ? k16 + 768 : z16, c4 = k16 + 1024;
    const uint64_t dqq = desc_q(q16);
    float sa[32], sb[32], o[8], m0, m1, l0 = 0.f, l1 = 0.f;
    uint32_t pa[16], pb[16];
    {
        float sc[32];
        uint32_t pc[16];
        wgmma_fence();
        wgmma_m64n64k16_ss0<0, 0>(sa, dqq, desc_k(c4));
        wgmma_m64n64k16_ss0<0, 0>(sc, dqq, desc_k(c0));
        wgmma_m64n64k16_ss0<0, 0>(sb, dqq, desc_k(c1));
        wgmma_commit();
        wgmma_wait<0>();
        fence_regs(sa);
        fence_regs(sb);
        fence_regs(sc);
#pragma unroll
        for (int i = 0; i < 32; i++) {
            const int ci = 8 * (i >> 2) + (i & 1) - 8 * ((i >> 1) & 1);
            sa[i] = (ci <= thr) ? sa[i] : (gc0 >= 0 ? sc[i] : -INFINITY);
        }
        float x0, x1;
        local_max(sa, m0, m1);
        local_max(sb, x0, x1);
        if (gc0 + 1 >= 0) { m0 = fmaxf(m0, x0); m1 = fmaxf(m1, x1); }
        quad_max(m0, m1);
        exp_pack(sa, pa, m0, m1, l0, l1, true);
#pragma unroll
        for (int i = 0; i < 16; i++) {
            const int ci = 8 * (i >> 1) - 8 * (i & 1);
            const uint32_t msk = (ci + 1 <= thr) ? 0xFFFFFFFFu : (ci <= thr ? 0xFFFFu : 0u);
            pc[i] = pa[i] & ~msk;
            pa[i] &= msk;
        }
        exp_pack(sb, pb, m0, m1, l0, l1, gc0 + 1 >= 0);
        pin(pb[0], l0, l1);
        wgmma_fence();
        pv_chunk<true>(o, pb, c1);
        pv_chunk<false>(o, pa, c4);
        pv_chunk<false>(o, pc, c0);
        wgmma_m64n64k16_ss0<0, 0>(sa, dqq, desc_k(c2));
        wgmma_m64n64k16_ss0<0, 0>(sb, dqq, desc_k(c3));
        wgmma_commit();
        wgmma_wait<0>();
        fence_regs(sa);
        fence_regs(sb);
        fence_regs(o);
    }
    {
        float x0 = m0, x1 = m1, y0, y1;
        local_max(sa, y0, y1);
        if (gc0 + 2 >= 0) { x0 = fmaxf(x0, y0); x1 = fmaxf(x1, y1); }
        local_max(sb, y0, y1);
        if (gc0 + 3 >= 0) { x0 = fmaxf(x0, y0); x1 = fmaxf(x1, y1); }
        quad_max(x0, x1);
        const float al0 = ex2(m0 - x0), al1 = ex2(m1 - x1);
        l0 *= al0; l1 *= al1;
        scale_o(o, al0, al1);
        m0 = x0; m1 = x1;
    }
    exp_pack(sa, pa, m0, m1, l0, l1, gc0 + 2 >= 0);
    exp_pack(sb, pb, m0, m1, l0, l1, gc0 + 3 >= 0);
    pin(pa[0], l0, l1);
    wgmma_fence();
    pv_chunk<false>(o, pa, c2);
    pv_chunk<false>(o, pb, c3);
    wgmma_commit();
    l0 += __shfl_xor_sync(0xffffffffu, l0, 1); l1 += __shfl_xor_sync(0xffffffffu, l1, 1);
    l0 += __shfl_xor_sync(0xffffffffu, l0, 2); l1 += __shfl_xor_sync(0xffffffffu, l1, 2);
    const float f0 = __fdividef(g0, l0), f1 = __fdividef(g1, l1);
    wg_bar(barid);
    wgmma_wait<0>();
    fence_regs(o);
    stmatrix4t(oad, pack_bf16(o[0] * f0, o[1] * f0), pack_bf16(o[2] * f1, o[3] * f1), pack_bf16(o[4] * f0, o[5] * f0),
               pack_bf16(o[6] * f1, o[7] * f1));
}

__device__ __forceinline__ void qk_first(float (&sa)[32], float (&sc)[32], uint32_t q16, uint32_t k16, uint32_t z16, int gc0) {
    wgmma_fence();
    wgmma_m64n64k16_ss0<0, 0>(sa, desc_q(q16), desc_k(k16 + 1024));
    wgmma_m64n64k16_ss0<0, 0>(sc, desc_q(q16), desc_k(gc0 >= 0 ? k16 : z16));
    wgmma_commit();
}
template <bool MERGED>
__device__ __forceinline__ void exp_pv(const float (&s)[32], uint32_t (&p)[16], uint32_t (&p2)[16], float (&o)[8], uint32_t a16, uint32_t b16,
                                       int thr, float& l0, float& l1, bool valid) {
    const uint64_t dv = desc_v(a16), dv2 = desc_v(b16);
    float t0 = l0, t1 = l1;
#pragma unroll
    for (int b = 0; b < 4; b++) {
#pragma unroll
        for (int j = 2 * b; j < 2 * b + 2; j++) {
            const float e0 = ex2(s[4 * j]), e1 = ex2(s[4 * j + 1]), e2 = ex2(s[4 * j + 2]), e3 = ex2(s[4 * j + 3]);
            t0 += e0 + e1;
            t1 += e2 + e3;
            p[2 * j] = pack_bf16(e0, e1);
            p[2 * j + 1] = pack_bf16(e2, e3);
        }
        if (b == 3) {
            l0 = valid ? t0 : l0;
            l1 = valid ? t1 : l1;
            pin(p[15], l0, l1);
        }
        if (MERGED) {
#pragma unroll
            for (int i = 4 * b; i < 4 * b + 4; i++) {
                const int ci = 8 * (i >> 1) - 8 * (i & 1);
                const uint32_t msk = (ci + 1 <= thr) ? 0xFFFFFFFFu : (ci <= thr ? 0xFFFFu : 0u);
                p2[i] = p[i] & ~msk;
                p[i] &= msk;
            }
        }
        wgmma_fence();
        if (MERGED && b == 0) wgmma_m64n16k16_rs0<0, 1>(o, p[0], p[1], p[2], p[3], dv);
        else wgmma_m64n16k16_rs<0, 1>(o, p[4 * b], p[4 * b + 1], p[4 * b + 2], p[4 * b + 3], dv + b * 64);
        if (MERGED) wgmma_m64n16k16_rs<0, 1>(o, p2[4 * b], p2[4 * b + 1], p2[4 * b + 2], p2[4 * b + 3], dv2 + b * 64);
    }
    wgmma_commit();
}
__device__ __forceinline__ bool attn_fast(float (&sa)[32], float (&sc)[32], uint32_t q16, uint32_t k16, uint32_t z16, int gc0, int thr,
                                          const float* gate, uint32_t oad, int barid, uint32_t nq16, uint32_t nk16, uint32_t nbar) {
    const uint32_t c0 = gc0 >= 0 ? k16 : z16, c1 = gc0 + 1 >= 0 ? k16 + 256 : z16, c2 = gc0 + 2 >= 0 ? k16 + 512 : z16,
                   c3 = gc0 + 3 >= 0 ? k16 + 768 : z16, c4 = k16 + 1024;
    const uint64_t dqq = desc_q(q16);
    float o[8], l0 = 0.f, l1 = 0.f;
    uint32_t pa[16], pb[16], pc[16];
#pragma unroll
    for (int i = 0; i < 32; i++) {
        const int ci = 8 * (i >> 2) + (i & 1) - 8 * ((i >> 1) & 1);
        sa[i] = (ci <= thr) ? sa[i] : (gc0 >= 0 ? sc[i] : -INFINITY);
    }
    wgmma_fence();
    wgmma_m64n64k16_ss0<0, 0>(sc, dqq, desc_k(c1));
    wgmma_commit();
    exp_pv<true>(sa, pa, pc, o, c4, c0, thr, l0, l1, true);
    wgmma_m64n64k16_ss0<0, 0>(sa, dqq, desc_k(c2));
    wgmma_commit();
    wgmma_wait<2>();
    fence_regs(sc);
    exp_pv<false>(sc, pb, pb, o, c1, c1, thr, l0, l1, gc0 + 1 >= 0);
    wgmma_wait<2>();
    wgmma_fence();
    wgmma_m64n64k16_ss0<0, 0>(sc, dqq, desc_k(c3));
    wgmma_commit();
    wgmma_wait<2>();
    fence_regs(sa);
    exp_pv<false>(sa, pa, pa, o, c2, c2, thr, l0, l1, gc0 + 2 >= 0);
    mbar_wait(nbar, 0);
    const float g0 = __ldcg(gate), g1 = __ldcg(gate + 8);
    wgmma_wait<1>();
    fence_regs(sc);
    exp_pv<false>(sc, pc, pc, o, c3, c3, thr, l0, l1, gc0 + 3 >= 0);
    qk_first(sa, sc, nq16, nk16, z16, gc0);
    l0 += __shfl_xor_sync(0xffffffffu, l0, 1); l1 += __shfl_xor_sync(0xffffffffu, l1, 1);
    l0 += __shfl_xor_sync(0xffffffffu, l0, 2); l1 += __shfl_xor_sync(0xffffffffu, l1, 2);
    uint32_t ok;
    const bool good = l0 >= 0x1p-40f && l0 <= 0x1p40f && l1 >= 0x1p-40f && l1 <= 0x1p40f;
    asm volatile("{\n.reg .pred p, q;\nsetp.ne.u32 p, %1, 0;\nbar.red.and.pred q, %2, 128, p;\nselp.u32 %0, 1, 0, q;\n}"
                 : "=r"(ok) : "r"((uint32_t)good), "r"(barid) : "memory");
    ok = __all_sync(0xffffffffu, ok);
    const float f0 = __fdividef(g0, l0), f1 = __fdividef(g1, l1);
    wgmma_wait<0>();
    fence_regs(o);
    fence_regs(sa);
    fence_regs(sc);
    if (ok) stmatrix4t(oad, pack_bf16(o[0] * f0, o[1] * f0), pack_bf16(o[2] * f1, o[3] * f1), pack_bf16(o[4] * f0, o[5] * f0),
                       pack_bf16(o[6] * f1, o[7] * f1));
    return ok != 0;
}

__device__ __forceinline__ int get_tile(uint32_t tilebar, uint32_t tileval) {
    mbar_wait_cluster(tilebar, 0);
    uint32_t v;
    asm volatile("ld.shared.u32 %0, [%1];" : "=r"(v) : "r"(tileval) : "memory");
    return (int)(v & 255);
}
__device__ __forceinline__ int get_parity(uint32_t tilebar, uint32_t tileval) {
    uint32_t v;
    asm volatile("ld.shared.u32 %0, [%1];" : "=r"(v) : "r"(tileval) : "memory");
    return (int)(v >> 8);
}
__device__ __forceinline__ void ticket(unsigned* flags) {
    asm volatile("red.relaxed.gpu.global.add.u32 [%0], 1;" ::"l"(flags + FL_DONE * FS) : "memory");
}

__global__ void __cluster_dims__(2, 1, 1) __launch_bounds__(512, 1)
fused_kernel(const __grid_constant__ Params P, const __grid_constant__ CUtensorMap tm_x, const __grid_constant__ CUtensorMap tm_wqkv,
             const __grid_constant__ CUtensorMap tm_w1, const __grid_constant__ CUtensorMap tm_h,
             const __grid_constant__ CUtensorMap tm_w2, const __grid_constant__ CUtensorMap tm_ut,
             const __grid_constant__ CUtensorMap tm_o, const __grid_constant__ CUtensorMap tm_wo,
             const __grid_constant__ CUtensorMap tm_ost,
             const __grid_constant__ CUtensorMap tm_ust, const __grid_constant__ CUtensorMap tm_w1k) {
    extern __shared__ __align__(1024) unsigned char smem_raw[];
    const uint32_t sbase = (smem_u32(smem_raw) + 1023) & ~1023u;
    const uint32_t bars = sbase + OFF_BAR;
    const uint32_t fullQ = bars, emptyQ = bars + 40, fullG = bars + 64, emptyG = bars + 104, kvfull = bars + 536, kvempty = bars + 160, h0full = bars + 144, h0issued = bars + 152, h0ok = bars + 192, h1full = bars + 368,
                   xready = bars + 176, lndone = bars + 184, udone = bars + 200, tilebar = bars + 208, tileval = bars + 216, auxok = bars + 320, kvfree = bars + 328, ownok = bars + 336, qhalf = bars + 352, lnok = bars + 560, hstaged = bars + 376, astaged = bars + 384, ustaged = bars + 392, ostaged = bars + 416, depok = bars + 224, h0staged = bars + 480, kvread = bars + 488, usent = bars + 496, kslot = bars + 504, aok = bars + 520, gstage = bars + 256;
    const int tid = threadIdx.x, wg = __shfl_sync(0xffffffffu, tid >> 7, 0), lane = tid & 31;
    const int c = blockIdx.x;
    const int rb = c >> 3, hg = c & 7;
    const int kh = c & 1;

    const uint32_t t_in = clock32();
    if (tid == 416) { prefetch_tmap(&tm_wqkv); prefetch_tmap(&tm_x); }
    if (__shfl_sync(0xffffffffu, tid >> 5, 0) == 12) {
        if (lane == 0) {
#pragma unroll
            for (int i = 0; i < 5; i++) mbar_init(fullQ + i * 8, 1);
            fence_async_smem();
        }
        __syncwarp();
#pragma unroll 1
        for (int k = 0; k < NFIRST; k++)
            load_stage(fullQ + k * 8, Q_BYTES, sbase + k * Q_BYTES + 16384, &tm_wqkv, hg * 64, k * 64, 0, sbase + k * Q_BYTES, &tm_x, 0, rb * 128, k);
    }
    if (wg == 3) {
        const int w = (tid >> 5) & 3;
        __syncthreads();
        asm volatile("barrier.cluster.arrive.relaxed.aligned;" ::: "memory");
        asm volatile("setmaxnreg.dec.sync.aligned.u32 40;");
        if (w == 0) {
#pragma unroll 1
            for (int k = NFIRST; k < 5; k++) {
                while (clock32() - t_in < (uint32_t)(D0 + (k - NFIRST) * DS)) {}
                load_stage(fullQ + k * 8, Q_BYTES, sbase + k * Q_BYTES + 16384, &tm_wqkv, hg * 64, k * 64, 0, sbase + k * Q_BYTES, &tm_x, 0, rb * 128, k);
            }
        }
        if (w != 2) mbar_wait(qhalf, 0);
        if (w == 0) {
#pragma unroll 1
            for (int k = 5; k < 8; k++) {
                const int s = k - 5;
                mbar_wait(emptyQ + s * 8, 0);
                load_stage(fullQ + s * 8, Q_BYTES, sbase + s * Q_BYTES + 16384, &tm_wqkv, hg * 64, k * 64, 0, sbase + s * Q_BYTES, &tm_x, 0, rb * 128, k);
            }
            asm volatile("barrier.cluster.wait.acquire.aligned;" ::: "memory");
            const int tile = __shfl_sync(0xffffffffu, get_tile(tilebar, tileval), 0);
            const int gm2 = (tile >> 2) * 2, dq2 = (tile & 3) * 2;
            const int par = __shfl_sync(0xffffffffu, get_parity(tilebar, tileval), 0);
            const uint32_t peer_xready = mapa(xready, kh ^ 1);
            uint32_t soff = 0, ph = 0;
            auto stage = [&](uint32_t bytes, const CUtensorMap* ta, int za, const CUtensorMap* tb, int y, int g, int boff) {
                mbar_wait(emptyG + soff, ph);
                load_g(fullG + soff, bytes, gslot(sbase, soff >> 3), ta, za, tb, dq2, y, g, g + boff);
                soff += 8;
                if (soff == NG * 8) { soff = 0; ph ^= 1; }
            };
            auto xslot = [&]() {
                mbar_wait(emptyG + soff, ph);
                if (lane == 0) { mbar_expect_tx(fullG + soff, 16384); mbar_arrive_remote(peer_xready); }
                __syncwarp();
                soff += 8;
                if (soff == NG * 8) { soff = 0; ph ^= 1; }
            };
            const unsigned* fp = lane == 7 ? P.flags + (FL_O + gm2 + kh) * FS : P.flags + (FL_U + kh * 7 + lane) * FS + (lane < NVAL ? 2 : 0);
            unsigned fv = lane < 8 ? flag_poll(fp) : 0;
            if (tile < 56) {
                mbar_wait(lnok, 0);
#pragma unroll 1
                for (int i = 0; i < 15; i++) {
                    if (i == NVAL) mbar_wait(lnok + 8, 0);
                    stage(G_BYTES, &tm_w1, gm2, &tm_h, 0, kh * 128 + i * 8, par * 256);
                }
                xslot();
#pragma unroll 1
                for (int i = 0; i < 2; i++) stage(24576, &tm_w1k, gm2 + kh, &tm_h, 0, i * 128 + 120, par * 256);
            }
            mbar_wait(auxok, 0);
            flags_wait(fp, 8, fv, lane == 7);
            stage(G_BYTES, &tm_o, gm2, &tm_wo, 0, kh * 32, 0);
            {
                uint32_t so = soff, p2 = ph;
#pragma unroll 1
                for (int j = 0; j < NG - 1; j++) {
                    if (j == HOLDJ && tile < 56) mbar_wait(usent, 0);
                    mbar_wait(emptyG + so, p2);
                    load_a(fullG + so, G_BYTES, gslot(sbase, so >> 3), &tm_w2, 0, kh * 56 + j * 8, gm2);
                    so += 8;
                    if (so == NG * 8) { so = 0; p2 ^= 1; }
                }
                if (tile < 56) mbar_wait(ustaged, 0);
                unsigned ready = 0;
#pragma unroll 1
                for (int j = 0; j < NG - 1; j++) {
                    if (!((ready >> j) & 1)) {
                        int it = 0;
                        do {
                            if (lane < 7 && fv < 8) fv = flag_poll(fp);
                            ready = __ballot_sync(0xffffffffu, fv >= 8);
                        } while (!((ready >> j) & 1) && ++it < POLL_LIMIT);
                        asm volatile("fence.acquire.gpu;" ::: "memory");
                        asm volatile("fence.proxy.async.global;" ::: "memory");
                    }
                    if ((j == 1 || j == NG - 2) && tile < 56) mbar_wait(j == 1 ? ustaged + 8 : udone, 0);
                    load_b(fullG + soff, gslot(sbase, soff >> 3) + 16384, &tm_ut, 0, par * 112 + kh * 56 + j * 8, dq2);
                    soff += 8;
                    if (soff == NG * 8) { soff = 0; ph ^= 1; }
                }
                flags_wait(fp, 8, fv, lane < 7);
                if (lane == 0) ticket(P.flags);
            }
            int ug = kh * 56 + 32;
#pragma unroll 1
            for (int seg = 0; seg < 3; seg++) {
                const int uend = kh * 56 + (seg == 1 ? 40 : 56);
#pragma unroll 1
                for (; ug < uend; ug += 8) stage(G_BYTES, &tm_w2, gm2, &tm_ut, seg == 0 ? 0 : 8, ug, par * 112);
                if (seg == 2) break;
                if (seg == 0) ug = kh * 56;
                mbar_wait(depok + seg * 8, 0);
                stage(G_BYTES, &tm_o, gm2, &tm_wo, 0, kh * 32 + 8 + seg * 8, 0);
            }
            xslot();
            const unsigned char* omb = P.llo + (size_t)(par * 64 + (gm2 + kh) * 2) * 8192;
            mbar_wait(depok + 16, 0);
#pragma unroll 1
            for (int i = 0; i < 2; i++) {
                mbar_wait(emptyG + soff, ph);
                if (lane == 0) { mbar_expect_tx(kslot + i * 8, 8192); bulk_g2s(gslot(sbase, soff >> 3), omb + i * 8192, 8192, kslot + i * 8); }
                __syncwarp();
                load_a(fullG + soff, 16384, gslot(sbase, soff >> 3) + 16384, &tm_wo, 0, i * 32 + 24, dq2);
                soff += 8;
                if (soff == NG * 8) { soff = 0; ph ^= 1; }
            }
        } else if (w == 1) {
            const unsigned* fp = P.flags + (FL_KV + c - 8 * lane) * FS;
            const bool act = lane >= 1 && lane <= 2 && rb >= lane;
            unsigned v0 = act ? flag_poll(fp) : 0;
            if (lane == 0) {
                mbar_wait(astaged, 0);
                bulk_s2g(P.wos + (size_t)((c >> 6) * 256 + ((c >> 2) & 3) * 64 + ((c >> 4) & 3) * 16 + (c & 3) * 4) * D_DIM, sbase + OFF_KV + Q_BYTES, 4096);
                bulk_s2g(P.gate + c * 16, gstage, 64);
                bulk_done();
                mbar_arrive(lndone);
                release_add(P.flags + (FL_AUX + rb) * FS, 1);
            }
            __syncwarp();
            const int lg0 = rb >= 2 ? 0 : 32 - rb * 16;
            const int tile = get_tile(tilebar, tileval), par = get_parity(tilebar, tileval);
            const unsigned char* mb = P.llkv + (size_t)(par * NCTA + c - 8 * lane) * 16384;
            if (lane == 0) mbar_expect_tx(h0full, (32 - lg0) * 512);
            mbar_wait(h0staged, 0);
            {
                bool pend = act;
#pragma unroll 1
                for (int it = 0; __any_sync(0xffffffffu, pend) && it < POLL_LIMIT; it++) {
                    if (pend && v0 < 1) v0 = flag_poll(fp);
                    if (pend && v0 >= 1) {
                        bulk_g2s(sbase + OFF_KV + (2 - lane) * 8192, mb, 8192, h0full);
                        pend = false;
                    }
                    __syncwarp();
                }
            }
            if (lane == 0) { mbar_arrive(h0issued); TL1(19); }
            mbar_wait(kvread, 0);
            flags_wait(fp + 1, 1, 0, act);
            if (lane == 0) mbar_expect_tx(h1full, (32 - lg0) * 512);
            if (act) bulk_g2s(sbase + OFF_KV + KV_SLOT + (2 - lane) * 8192, mb + 8192, 8192, h1full);
            __syncwarp();
            mbar_wait(h1full, 0);
#pragma unroll 1
            for (int i = lg0 >> 4; i < 2; i++)
                ll_check<8>(sbase + OFF_KV + KV_SLOT + i * 8192, P.llkv + (size_t)(par * NCTA + c - 16 + i * 8) * 16384 + 8192, lane);
            __syncwarp();
            mbar_wait(auxok, 0);
            if (lane == 0) mbar_arrive(kvfull);
            flags_wait(fp + 2, 1, 0, act);
            if (lane == 0) {
                ticket(P.flags);
                const unsigned char* src = P.kv + ((size_t)(hg * 4) * 256 + rb * 16 - 32 + lg0) * 512;
#pragma unroll 1
                for (int hh = 2; hh < 4; hh++) {
                    const int slot = hh & 1;
                    const uint32_t bytes = (uint32_t)(48 - lg0) * 512u;
                    mbar_wait(kvempty + slot * 8, 0);
                    mbar_expect_tx(kvfull + (hh - 1) * 8, bytes);
                    bulk_g2s(sbase + OFF_KV + slot * KV_SLOT + lg0 * 512, src + (size_t)hh * 256 * 512, bytes, kvfull + (hh - 1) * 8);
                }
            }
            __syncwarp();
            mbar_wait(depok, 0);
            const uint4 z = make_uint4(0, 0, 0, 0);
            const int np = par ^ 1;
#pragma unroll 1
            for (int i = 0; i < 32; i++) *reinterpret_cast<uint4*>(P.llkv + (size_t)(np * NCTA + c) * 16384 + i * 512 + lane * 16) = z;
#pragma unroll 1
            for (int i = 0; i < 8; i++)
                *reinterpret_cast<uint4*>(P.llo + (size_t)((np * 32 + rb * 2 + (i >> 2)) * 2 + (hg >> 2)) * 8192 + (hg & 3) * 2048 + (i & 3) * 512 + lane * 16) = z;
            if (((c >> 2) & 15) < NVAL) {
#pragma unroll 1
                for (int i = 0; i < 32; i++) *reinterpret_cast<uint4*>(P.h + (size_t)(np * S_LEN + c * 16) * D_DIM + i * 256 + lane * 8) = z;
            }
            if (tile < 56 && (tile >> 2) % 7 < NVAL) {
#pragma unroll 1
                for (int i = 0; i < 16; i++) {
                    const int r = i * 2 + (lane >> 4);
                    *reinterpret_cast<uint4*>(P.ut + (size_t)(np * F_DIM + (tile >> 2) * 128 + kh * 64 + (r >> 3) * 16 + (r & 7)) * D_DIM + (tile & 3) * 128 + (lane & 15) * 8) = z;
                }
            }
        } else if (w == 2) {
            if (lane == 0) {
                prefetch_tmap(&tm_w1); prefetch_tmap(&tm_h); prefetch_tmap(&tm_w2); prefetch_tmap(&tm_ut); prefetch_tmap(&tm_o);
                prefetch_tmap(&tm_wo); prefetch_tmap(&tm_ost); prefetch_tmap(&tm_ust); prefetch_tmap(&tm_w1k);
                const int par = flag_poll(P.epoch) & 1;
                mbar_wait(hstaged, 0);
                bulk_s2g(P.h + (size_t)(par * S_LEN + c * 16) * D_DIM, sbase + OFF_X, 16384);
                bulk_done();
                mbar_arrive(lndone);
                if (((c >> 2) & 15) < NVAL) hint_add(P.flags + (FL_LN + (c >> 2)) * FS);
                else release_add(P.flags + (FL_LN + (c >> 2)) * FS, 1);
                TL1(23);
                unsigned char* dst = P.kv + ((size_t)(hg * 4) * 256 + rb * 16) * 512;
                unsigned char* mb = P.llkv + (size_t)(par * NCTA + c) * 16384;
                mbar_wait(h0staged, 0);
                bulk_s2g(mb, sbase + OFF_KV + 16384, 8192);
                bulk_done();
                if (rb < 15) hint_add(P.flags + (FL_KV + c) * FS);
                TL1(24);
                mbar_wait(h0issued, 0);
                mbar_wait(ownok, 0);
                bulk_s2g(mb + 8192, sbase + OFF_KV + KV_SLOT + 16384, 8192);
                bulk_s2g(dst + 2 * 256 * 512, sbase + OFF_KV + KV_SLOT, 8192);
                bulk_s2g(dst + 3 * 256 * 512, sbase + OFF_KV + KV_SLOT + 8192, 8192);
                bulk_done();
                mbar_arrive(kvread);
                if (rb < 15) { hint_add(P.flags + (FL_KV + c) * FS + 1); release_add(P.flags + (FL_KV + c) * FS + 2, 1); }
                const int tile = get_tile(tilebar, tileval);
                if (tile < 56) {
                    const uint32_t st = gslot(sbase, 17 % NG) + 16384;
#pragma unroll 1
                    for (int p = 0; p < 2; p++) {
                        mbar_wait(ustaged + p * 8, 0);
                        tma4d_store(&tm_ust, st + p * 8192, p * 8, par * 112 + (tile >> 2) * 8 + kh * 4, (tile & 3) * 2);
                        if (p == 0) mbar_arrive(usent);
                        bulk_done();
                        if (p == 1) mbar_arrive(udone);
                        if (p == 0 && (tile >> 2) % 7 < NVAL) hint_add(P.flags + (FL_U + (tile >> 2)) * FS + 2);
                        else release_add(P.flags + (FL_U + (tile >> 2)) * FS + p, 1);
                        if (p == 0) TL1(95);
                    }
                    TL1(25);
                }
            }
            __syncwarp();
            {
                const unsigned* op = P.flags + (FL_O + (get_tile(tilebar, tileval) >> 2) * 2 + kh) * FS;
                flags_wait(lane < 7 ? P.flags + (FL_U + kh * 7 + lane) * FS + 1 : op + 1, 8, 0, lane < 8);
                if (lane == 0) mbar_arrive(depok);
                flags_wait(op + 2, 8, 0, lane == 0);
                if (lane == 0) mbar_arrive(depok + 8);
                flags_wait(op + (kh ^ 1) * FS * lane - kh * FS * lane + 3, 8, 0, lane < 2);
                if (lane == 0) { mbar_arrive(depok + 16); ticket(P.flags); }
            }
        } else {
            asm volatile("barrier.cluster.wait.acquire.aligned;" ::: "memory");
            if (kh == 0 && lane == 0) {
                uint32_t smid;
                asm("mov.u32 %0, %%smid;" : "=r"(smid));
                const unsigned ep = flag_poll(P.epoch);
                int b = (smid >> 1) < 72 ? P.bucket[smid >> 1] : 15;
                unsigned t = atom_inc(P.flags + (FL_CLAIM + b) * FS);
                if (t >= 4) {
                    const uint32_t t0 = clock32();
                    while (clock32() - t0 < 2000) {}
                    b = 16;
#pragma unroll 1
                    do { b--; t = atom_inc(P.flags + (FL_CLAIM + b) * FS); } while (t >= 4 && b > 0);
                }
                const uint32_t tile = b * 4 + (t & 3) + ((ep & 1) << 8);
                TL1(148);
#pragma unroll
                for (int rk = 0; rk < 2; rk++)
                    asm volatile("st.async.weak.shared::cluster.mbarrier::complete_tx::bytes.u32 [%0], %1, [%2];"
                                 ::"r"(mapa(tileval, rk)), "r"(tile), "r"(mapa(tilebar, rk)) : "memory");
            }
            __syncwarp();
            {
                const unsigned* fp = P.flags + (FL_LN + (lane < 16 ? kh * 16 + lane : (kh ^ 1) * 16 + 15)) * FS;
                flags_wait(fp, 4, 0, lane < NVAL);
                if (lane == 0) { mbar_arrive(lnok); TL1(145); }
                flags_wait(fp, 4, 0, lane < 17);
                if (lane == 0) mbar_arrive(lnok + 8);
                flags_wait(P.flags + (FL_AUX + lane) * FS, 8, 0, lane < 16);
                if (lane == 0) {
                    mbar_arrive(auxok);
                    ticket(P.flags);
#pragma unroll 1
                    for (int hh = 0; hh < 3; hh++) {
                        mbar_wait(ostaged + hh * 8, 0);
                        tma3d_store(&tm_ost, sbase + OFF_X + hh * 2048, 0, (hg >> 2) * 256 + hh * 64 + (hg & 3) * 16, rb * 2);
                        tma3d_store(&tm_ost, sbase + OFF_X + 8192 + hh * 2048, 0, (hg >> 2) * 256 + hh * 64 + (hg & 3) * 16, rb * 2 + 1);
                        bulk_done();
                        release_add(P.flags + (FL_O + rb * 2 + (hg >> 2)) * FS + hh, 2);
                    }
                }
                __syncwarp();
            }
          if (c == 0) {
            const unsigned v0 = lane == 0 ? flag_poll(P.flags + FL_DONE * FS) : 0;
            if (lane == 0) flag_wait(P.flags + FL_DONE * FS, 4 * NCTA, v0);
            __syncwarp();
            for (int i = lane; i < NFLAGS; i += 32) *reinterpret_cast<uint4*>(P.flags + i * FS) = make_uint4(0, 0, 0, 0);
            if (lane == 0) hint_add(P.epoch);
          }
        }
    } else if (wg == 0) {
        const int w = tid >> 5, a = lane >> 2, q = lane & 3;
        __syncthreads();
        asm volatile("barrier.cluster.arrive.relaxed.aligned;" ::: "memory");
        asm volatile("setmaxnreg.inc.sync.aligned.u32 168;");
        {
            const int lr = w * 4 + (lane >> 3), j8 = lane & 7;
            uint4 xv[8], gv[8];
#pragma unroll
            for (int i = 0; i < 8; i++) gv[i] = __ldg(reinterpret_cast<const uint4*>(P.gw) + i * 8 + j8);
            const uint4* xsrc = reinterpret_cast<const uint4*>(P.x + (size_t)(c * 16 + lr) * D_DIM) + j8;
            while (clock32() - t_in < (uint32_t)DL) {}
#pragma unroll
            for (int i = 0; i < 8; i++)
                asm volatile("ld.global.nc.v4.u32 {%0,%1,%2,%3}, [%4];" : "=r"(xv[i].x), "=r"(xv[i].y), "=r"(xv[i].z), "=r"(xv[i].w) : "l"(xsrc + i * 8) : "memory");
            TL(20);
            float f[64];
            const uint32_t* xp = reinterpret_cast<const uint32_t*>(xv);
            const uint32_t* gp = reinterpret_cast<const uint32_t*>(gv);
            float s0 = 0.f, s1 = 0.f, s2 = 0.f, s3 = 0.f, d0 = 0.f, d1 = 0.f;
#pragma unroll
            for (int i = 0; i < 32; i += 2) {
                f[2 * i] = bf_lo(xp[i]); f[2 * i + 1] = bf_hi(xp[i]); f[2 * i + 2] = bf_lo(xp[i + 1]); f[2 * i + 3] = bf_hi(xp[i + 1]);
                s0 += f[2 * i]; s1 += f[2 * i + 1]; s2 += f[2 * i + 2]; s3 += f[2 * i + 3];
                d0 = fmaf(f[2 * i], bf_lo(gp[i]), d0); d1 = fmaf(f[2 * i + 1], bf_hi(gp[i]), d1);
                d0 = fmaf(f[2 * i + 2], bf_lo(gp[i + 1]), d0); d1 = fmaf(f[2 * i + 3], bf_hi(gp[i + 1]), d1);
            }
            float sum = (s0 + s1) + (s2 + s3), dot = d0 + d1;
#pragma unroll
            for (int o = 1; o < 8; o <<= 1) { sum += __shfl_xor_sync(0xffffffffu, sum, o); dot += __shfl_xor_sync(0xffffffffu, dot, o); }
            TL(21);
            const float mean = sum * (1.f / D_DIM);
            s0 = s1 = s2 = s3 = 0.f;
#pragma unroll
            for (int i = 0; i < 64; i += 4) {
                f[i] -= mean; f[i + 1] -= mean; f[i + 2] -= mean; f[i + 3] -= mean;
                s0 = fmaf(f[i], f[i], s0); s1 = fmaf(f[i + 1], f[i + 1], s1); s2 = fmaf(f[i + 2], f[i + 2], s2); s3 = fmaf(f[i + 3], f[i + 3], s3);
            }
            float var = (s0 + s1) + (s2 + s3);
#pragma unroll
            for (int o = 1; o < 8; o <<= 1) var += __shfl_xor_sync(0xffffffffu, var, o);
            const float rstd = rsqrtf(var * (1.f / D_DIM) + 1e-5f);
#pragma unroll
            for (int i = 0; i < 8; i++)
                sts128_marked(sbase + OFF_X + lr * 1024 + (i * 8 + j8) * 16, pack_bf16(f[8 * i + 0] * rstd, f[8 * i + 1] * rstd),
                       pack_bf16(f[8 * i + 2] * rstd, f[8 * i + 3] * rstd), pack_bf16(f[8 * i + 4] * rstd, f[8 * i + 5] * rstd),
                       pack_bf16(f[8 * i + 6] * rstd, f[8 * i + 7] * rstd));
            fence_async_smem();
            __syncwarp();
            if (lane == 0) mbar_arrive(hstaged);
            TL(22);
            if (j8 == 0) sts32(gstage + lr * 4, __float_as_uint(2.f * __expf(fminf(fmaxf(dot, -60.f), 60.f))));
            if (lane < 16) {
                uint4 wv[4];
                const uint4* src = reinterpret_cast<const uint4*>(P.wo + (size_t)(c * 4 + w) * D_DIM + lane * 32);
#pragma unroll
                for (int i = 0; i < 4; i++) asm volatile("ld.global.nc.v4.u32 {%0,%1,%2,%3}, [%4];" : "=r"(wv[i].x), "=r"(wv[i].y), "=r"(wv[i].z), "=r"(wv[i].w) : "l"(src + i) : "memory");
                const uint32_t dst = sbase + OFF_KV + Q_BYTES + w * 1024 + lane * 64;
                sts128(dst, wv[0].x, wv[1].x, wv[2].x, wv[3].x);
                sts128(dst + 16, wv[0].y, wv[1].y, wv[2].y, wv[3].y);
                sts128(dst + 32, wv[0].z, wv[1].z, wv[2].z, wv[3].z);
                sts128(dst + 48, wv[0].w, wv[1].w, wv[2].w, wv[3].w);
            }
            fence_async_smem();
            __syncwarp();
            if (lane == 0) mbar_arrive(astaged);
        }
        TL(0);
        asm volatile("barrier.cluster.wait.acquire.aligned;" ::: "memory");
        float snd[64], keep[64];
        Ring r{0, 0};
        const int tile = __shfl_sync(0xffffffffu, get_tile(tilebar, tileval), 0), gm = tile >> 2, dq = tile & 3;
        const bool has_g1 = gm < 14;
        const int krow = gm * 128 + kh * 64 + w * 16 + a;
        const uint32_t koff = kh * 512, soff = (kh ^ 1) * 512;
        const float bb0 = has_g1 ? __bfloat162float(P.b1[krow]) : 0.f, bb1 = has_g1 ? __bfloat162float(P.b1[krow + 8]) : 0.f;
        const float bb2 = 2.f * __bfloat162float(P.b2[krow]), bb3 = 2.f * __bfloat162float(P.b2[krow + 8]);
#pragma unroll 1
        for (int phase = has_g1 ? 0 : 1; phase < 2; phase++) {
            {
                const float b0 = phase == 0 ? bb0 : bb2, b1 = phase == 0 ? bb1 : bb3;
                zero_regs(snd);
#pragma unroll
                for (int j = 0; j < 16; j++) { keep[4 * j] = keep[4 * j + 1] = b0; keep[4 * j + 2] = keep[4 * j + 3] = b1; }
            }
            int prev = 0;
            const int nmain = phase == 0 ? 13 : 15;
            auto gchk = [&](int k) {
                const int tp = get_tile(tilebar, tileval), pr = get_parity(tilebar, tileval);
                return reinterpret_cast<const unsigned char*>(phase == 0 ? P.h + (size_t)(pr * S_LEN + kh * 1024 + k * 64) * D_DIM + (tp & 3) * 128
                                                                         : P.ut + (size_t)(pr * F_DIM + kh * 896 + (k - 1) * 128) * D_DIM + (tp & 3) * 128);
            };
            if (phase == 0) {
                mbar_wait(fullG, 0);
                ll_check_tile(gslot(sbase, 0) + 16384, [&] { return gchk(0); }, 8192, w, lane);
            }
#pragma unroll 1
            for (int k = 0; k < nmain; k++) {
                mbar_wait(fullG + r.s * 8, r.ph);
                const uint32_t st = gslot(sbase, r.s);
                const uint64_t da = make_desc(st), db = make_desc(st + 16384);
                const bool chk = k + 1 < phase + NVAL;
#pragma unroll
                for (int kk = 0; kk < 4; kk++) {
                    wgmma_fence();
                    wgmma_m64n128k16_ss<1, 1>(snd, da + soff + kk * 128, db + kk * 128);
                    wgmma_m64n128k16_ss<1, 1>(keep, da + koff + kk * 128, db + kk * 128);
                    wgmma_commit();
                    if (kk == 0 || (kk < 3 && !chk)) wgmma_wait<1>();
                    if (kk == 0 && k > 0 && lane == 0) mbar_arrive_n(emptyG + prev * 8, 2);
                }
                prev = r.s;
                ring_adv(r);
                if (chk) {
                    mbar_wait(fullG + r.s * 8, r.ph);
                    ll_check_tile(gslot(sbase, r.s) + 16384, [&] { return gchk(k + 1); }, 8192 << phase, w, lane);
                }
            }
            TL(1 + phase * 3);
            float e0 = 0.f, e1 = 0.f;
            if (phase == 1) { e0 = __ldcg(P.gate + krow); e1 = __ldcg(P.gate + krow + 8); }
            uint64_t dt[2];
            uint32_t eb[4];
#pragma unroll
            for (int j = 0; j < 2; j++) {
                mbar_wait(fullG + r.s * 8, r.ph);
                TL(64 + phase * 4 + j);
                dt[j] = make_desc(gslot(sbase, r.s));
                eb[j] = emptyG + r.s * 8;
                wgmma_fence();
                mma4(snd, dt[j] + soff, dt[j] + 1024);
                wgmma_commit();
                if (j == 0) {
                    wgmma_wait<1>();
                    if (lane == 0) mbar_arrive_n(emptyG + prev * 8, 2);
                }
                ring_adv(r);
            }
            const uint32_t st = gslot(sbase, r.s), fb = fullG + r.s * 8, fph = r.ph;
            const uint32_t rdst = mapa(st + 16384 + tid * 16, kh ^ 1), rbar = mapa(fb, kh ^ 1);
            ring_adv(r);
            wgmma_fence();
            mma4(keep, dt[0] + koff, dt[0] + 1024);
            mma4(keep, dt[1] + koff, dt[1] + 1024);
            wgmma_commit();
            mbar_wait_cluster(xready, has_g1 ? phase : 0);
            wgmma_wait<1>();
            fence_regs(snd);
#pragma unroll
            for (int i = 0; i < 8; i++) send1(snd, i, rdst, rbar);
#pragma unroll
            for (int j = 2; j < 4; j++) {
                mbar_wait(fullG + r.s * 8, r.ph);
                mbar_wait(aok + (j - 2) * 8, phase ^ 1);
                TL(64 + phase * 4 + j);
                const uint64_t d = make_desc(gslot(sbase, r.s));
                eb[j] = emptyG + r.s * 8;
                wgmma_fence();
                mma4(keep, d, d + 1024);
                wgmma_commit();
                if (j == 2) {
                    wgmma_wait<1>();
                    if (lane == 0) { mbar_arrive_n(eb[0], 2); mbar_arrive_n(eb[1], 2); }
                }
                ring_adv(r);
            }
            uint4 px[4];
            const uint32_t xsrc = st + 16384 + tid * 16;
            mbar_wait_cluster(fb, fph);
#pragma unroll
            for (int i = 0; i < 4; i++) px[i] = lds128(xsrc + i * 2048);
            e0 = __fdividef(1.f, 2.f + e0); e1 = __fdividef(1.f, 2.f + e1);
            wgmma_wait<0>();
            fence_regs(keep);
            TL(5 + phase * 8);
            if (phase == 0) {
                wg_bar(1);
                if (lane == 0) { mbar_arrive_n(fb + (emptyG - fullG), 2); mbar_arrive_n(eb[2], 2); mbar_arrive_n(eb[3], 2); }
                const uint32_t rowa = gslot(sbase, 17 % NG) + 16384 + (w * 8 + a) * 128;
#pragma unroll
                for (int p = 0; p < 2; p++) {
#pragma unroll
                    for (int jj = 0; jj < 4; jj++) {
                        add1(keep, p * 4 + jj, px[jj]);
                        const float* t = &keep[jj * 16 + p * 2];
                        const uint32_t u0 = pack_bf16(gelu_tanh(t[0]), gelu_tanh(t[1])), u1 = pack_bf16(gelu_tanh(t[4]), gelu_tanh(t[5])),
                                       u2 = pack_bf16(gelu_tanh(t[8]), gelu_tanh(t[9])), u3 = pack_bf16(gelu_tanh(t[12]), gelu_tanh(t[13]));
                        const uint32_t ad = rowa + p * 8192 + (jj >> 1) * 4096 + ((((jj & 1) * 4 + q) ^ a) << 4);
                        if (p == 0) sts128_marked(ad, u0, u1, u2, u3); else sts128(ad, u0, u1, u2, u3);
                    }
                    fence_async_smem();
                    __syncwarp();
                    if (lane == 0) mbar_arrive(ustaged + p * 8);
                    if (p == 0) {
#pragma unroll
                        for (int i = 0; i < 4; i++) px[i] = lds128(xsrc + (4 + i) * 2048);
                        TL(2);
                    }
                }
                TL(3);
            } else {
                __nv_bfloat16* op = P.out + (size_t)krow * D_DIM + dq * 128 + q * 8;
                uint4 py[4];
#pragma unroll
                for (int i = 0; i < 4; i++) py[i] = lds128(xsrc + (4 + i) * 2048);
#pragma unroll
                for (int jj = 0; jj < 4; jj++) {
                    add1(keep, jj, px[jj]);
                    const float* t = &keep[jj * 16];
                    *reinterpret_cast<uint4*>(op + jj * 32) = make_uint4(pack_bf16(t[0] * e0, t[1] * e0), pack_bf16(t[4] * e0, t[5] * e0),
                                                                        pack_bf16(t[8] * e0, t[9] * e0), pack_bf16(t[12] * e0, t[13] * e0));
                }
#pragma unroll
                for (int jj = 0; jj < 4; jj++) {
                    add1(keep, 4 + jj, py[jj]);
                    const float* t = &keep[jj * 16];
                    *reinterpret_cast<uint4*>(op + 8 * D_DIM + jj * 32) = make_uint4(pack_bf16(t[2] * e1, t[3] * e1), pack_bf16(t[6] * e1, t[7] * e1),
                                                                                    pack_bf16(t[10] * e1, t[11] * e1), pack_bf16(t[14] * e1, t[15] * e1));
                }
                TL(7);
            }
        }
    } else {
        if (tid == 128) {
            for (int i = 0; i < 3; i++) mbar_init(emptyQ + i * 8, 8);
            for (int i = 0; i < NG; i++) { mbar_init(fullG + i * 8, 1); mbar_init(emptyG + i * 8, 8); }
            for (int i = 0; i < 3; i++) mbar_init(kvfull + i * 8, 1);
            mbar_init(kvempty, 8); mbar_init(kvempty + 8, 8); mbar_init(h0full, 1); mbar_init(h0issued, 1); mbar_init(h0ok, 8);
            mbar_init(xready, 1); mbar_init(lndone, 2); mbar_init(hstaged, 4); mbar_init(astaged, 4); mbar_init(ustaged, 4); mbar_init(ustaged + 8, 4); mbar_init(auxok, 1); mbar_init(kvfree, 8); mbar_init(ownok, 8); mbar_init(h0staged, 8); mbar_init(kvread, 1); mbar_init(kslot, 1); mbar_init(kslot + 8, 1); mbar_init(aok, 4); mbar_init(aok + 8, 4); mbar_init(usent, 1); mbar_init(qhalf, 1); mbar_init(lnok, 1); mbar_init(lnok + 8, 1); mbar_init(h1full, 1);
            for (int i = 0; i < 4; i++) mbar_init(depok + i * 8, 1);
            for (int i = 0; i < 3; i++) mbar_init(ostaged + i * 8, 8);
            mbar_init(ostaged + 24, 4); mbar_init(ostaged + 32, 4);
            mbar_init(udone, 1);
            mbar_init(tilebar, 1); mbar_expect_tx(tilebar, 4);
            asm volatile("fence.mbarrier_init.release.cluster;" ::: "memory");
            fence_async_smem();
        }
        TLA(140);
        __syncthreads();
        TLA(141);
        asm volatile("barrier.cluster.arrive.relaxed.aligned;" ::: "memory");
        TLA(142);
        asm volatile("setmaxnreg.inc.sync.aligned.u32 152;");
        TLA(143);
        const int half = wg - 1, w = (tid >> 5) & 3, a = lane >> 2, q = lane & 3;
        const uint32_t xb = sbase + OFF_X + half * 8192;
        {
            float acc[96];
            zero_regs(acc);
            fence_regs(acc);
            TLA(144);
#pragma unroll 1
            for (int k = 0; k < 8; k++) {
                const int s = k < 5 ? k : k - 5;
                mbar_wait(fullQ + s * 8, k >= 5);
                if (k == 0 && tid == 128) mbar_arrive(qhalf);
                TLA(72 + k);
                wgmma_fence();
                const uint32_t st = sbase + s * Q_BYTES;
                const uint64_t da = make_desc(st + half * 8192), db = make_desc(st + 16384);
#pragma unroll
                for (int kk = 0; kk < 4; kk++) wgmma_m64n192k16_ss<0, 1>(acc, da + kk * 2, db + kk * 128);
                wgmma_commit();
                wgmma_wait<1>();
                if (k > 0 && lane == 0) mbar_arrive(k <= 3 ? emptyQ + (k - 1) * 8 : k == 4 ? emptyG : k == 5 ? kvfree : emptyG + (k - 5) * 8);
            }
            mbar_wait(kvfree, 0);
            mbar_wait(lndone, 0);
            wgmma_wait<0>();
            fence_regs(acc);
            TLA(9);
            const uint32_t lofs = (w * 2 + ((lane >> 3) & 1)) * 512 + (lane >> 4) * 128 + (lane & 7) * 16;
            const uint32_t kv01 = sbase + OFF_KV + 16384 + half * 4096, kv23 = sbase + OFF_KV + KV_SLOT + half * 4096;
#pragma unroll
            for (int hh = 0; hh < 4; hh++) {
                const uint32_t ad = lofs + (hh < 2 ? kv01 + hh * KV_SLOT : kv23 + (hh - 2) * 8192);
                const float* kk = &acc[32 + hh * 8];
                const float* kv = &acc[64 + hh * 8];
                uint32_t pk[8];
#pragma unroll
                for (int i = 0; i < 4; i++) {
                    pk[i] = pack_bf16(kk[2 * i], kk[2 * i + 1]); pk[4 + i] = pack_bf16(kv[2 * i], kv[2 * i + 1]);
                    if (hh < 2) { pk[i] = nz(pk[i]); pk[4 + i] = nz(pk[4 + i]); }
                }
                stmatrix4(ad, pk[0], pk[1], pk[2], pk[3]);
                stmatrix4(ad + 256, pk[4], pk[5], pk[6], pk[7]);
                if (hh == 0) {
                    fence_async_smem();
                    __syncwarp();
                    if (lane == 0) mbar_arrive(h0staged);
                }
            }
            if (lane == 0) { mbar_arrive(emptyG + 24); mbar_arrive(emptyG + 32); }
            if (rb < 2) sts128(sbase + OFF_KV + (tid - 128) * 16, 0, 0, 0, 0);
            const uint32_t qad = xb + (w * 2 + ((lane >> 3) & 1)) * 256 + (lane >> 4) * 128 + (lane & 7) * 16;
#pragma unroll
            for (int hh = 0; hh < 4; hh++) {
                const float* kq = &acc[hh * 8];
                stmatrix4(qad + hh * 2048, pack_bf16(kq[0] * SM_C, kq[1] * SM_C), pack_bf16(kq[2] * SM_C, kq[3] * SM_C),
                          pack_bf16(kq[4] * SM_C, kq[5] * SM_C), pack_bf16(kq[6] * SM_C, kq[7] * SM_C));
            }
            fence_async_smem();
            __syncwarp();
            if (lane == 0) mbar_arrive(ownok);
            mbar_wait_cluster(tilebar, 0);
            const int par = get_parity(tilebar, tileval);
            TLA(80);
            mbar_wait(h0full, 0);
            if (rb - 2 + half >= 0) {
                ll_check<2>(sbase + OFF_KV + half * 8192 + w * 2048, P.llkv + (size_t)(par * NCTA + c - 16 + half * 8) * 16384 + w * 2048, lane);
            }
            __syncwarp();
            if (lane == 0) mbar_arrive(h0ok);
            mbar_wait(h0ok, 0);
        }
        asm volatile("barrier.cluster.wait.acquire.aligned;" ::: "memory");
        TLA(10);
        {
            const int thr = 16 * w + a - 2 * q;
            const int gc0 = rb * 2 + half - 4;
            const int row = rb * 128 + half * 64 + w * 16 + a;
            const uint32_t oad = xb + ((lane >> 4) * 8 + (lane & 7)) * 128 + (((2 * w + ((lane >> 3) & 1)) ^ (lane & 7)) << 4);
            const uint32_t z16 = ((sbase + OFF_KV) & 0x3FFFF) >> 4, kb16 = z16 + half * 256, qb16 = (xb & 0x3FFFF) >> 4;
            float sa[32], sc[32];
            TLA(81);
            qk_first(sa, sc, qb16, kb16, z16, gc0);
            wgmma_wait<0>();
            fence_regs(sa);
            fence_regs(sc);
#pragma unroll 1
            for (int hh = 0; hh < 4; hh++) {
                const int slot = hh & 1, nh = hh < 3 ? hh + 1 : 3;
                const uint32_t k16 = kb16 + slot * (KV_SLOT / 16), q16 = qb16 + hh * 128;
                const uint32_t nk16 = kb16 + (nh & 1) * (KV_SLOT / 16), nq16 = qb16 + nh * 128;
                TLA(82 + hh);
                if (!attn_fast(sa, sc, q16, k16, z16, gc0, thr, P.gate + row, oad + hh * 2048, 1 + wg, nq16, nk16,
                               kvfull + (nh - 1) * 8)) {
                    const uint32_t k2 = __shfl_sync(0xffffffffu, k16, 0), q2 = __shfl_sync(0xffffffffu, q16, 0), z2 = __shfl_sync(0xffffffffu, z16, 0);
                    int thr2 = thr;
                    asm volatile("" : "+r"(thr2));
                    attn_safe(q2, k2, z2, gc0, thr2, __ldcg(P.gate + row), __ldcg(P.gate + row + 8), oad + hh * 2048, 1 + wg);
                    qk_first(sa, sc, __shfl_sync(0xffffffffu, nq16, 0), __shfl_sync(0xffffffffu, nk16, 0), z2, gc0);
                    wgmma_wait<0>();
                    fence_regs(sa);
                    fence_regs(sc);
                }
                if (hh == 3) { __syncwarp(); ll_mark(oad + 3 * 2048); }
                fence_async_smem();
                __syncwarp();
                if (lane == 0) { mbar_arrive(kvempty + slot * 8); mbar_arrive(ostaged + (hh == 3 ? 3 + half : hh) * 8); }
            }
            TLA(11);
            const int par = get_parity(tilebar, tileval), t = tid & 127, tile = get_tile(tilebar, tileval);
            if (t == 0) {
                mbar_wait(ostaged + (3 + half) * 8, 0);
                bulk_s2g(P.llo + (size_t)((par * 32 + rb * 2 + half) * 2 + (hg >> 2)) * 8192 + (hg & 3) * 2048, xb + 3 * 2048, 2048);
                bulk_done();
                hint_add(P.flags + (FL_O + rb * 2 + (hg >> 2)) * FS + 3);
                TL1(12);
            }
            __syncwarp();
            mbar_wait(kslot + half * 8, 0);
            ll_check<2>(gslot(sbase, ((tile < 56 ? 36 : 18) + half) % NG) + w * 2048,
                        P.llo + (size_t)((par * 32 + (tile >> 2) * 2 + kh) * 2 + half) * 8192 + w * 2048, lane);
            __syncwarp();
            if (lane == 0) mbar_arrive(aok + half * 8);
        }
    }
}

typedef CUresult (*EncodeFn)(CUtensorMap*, CUtensorMapDataType, cuuint32_t, void*, const cuuint64_t*, const cuuint64_t*,
                             const cuuint32_t*, const cuuint32_t*, CUtensorMapInterleave, CUtensorMapSwizzle,
                             CUtensorMapL2promotion, CUtensorMapFloatOOBfill);

CUtensorMap make_map(EncodeFn enc, const void* ptr, const cuuint64_t* dims, const cuuint64_t* strides, const cuuint32_t* box) {
    CUtensorMap m;
    cuuint32_t es[3] = {1, 1, 1};
    enc(&m, CU_TENSOR_MAP_DATA_TYPE_BFLOAT16, 3, const_cast<void*>(ptr), dims, strides, box, es, CU_TENSOR_MAP_INTERLEAVE_NONE,
        CU_TENSOR_MAP_SWIZZLE_128B, CU_TENSOR_MAP_L2_PROMOTION_L2_128B, CU_TENSOR_MAP_FLOAT_OOB_FILL_NONE);
    return m;
}
CUtensorMap map_chunks(EncodeFn enc, const void* p, int rows, int cols, int brows, int bch) {
    cuuint64_t d[3] = {64, (cuuint64_t)rows, (cuuint64_t)(cols / 64)}, s[2] = {(cuuint64_t)cols * 2, 128};
    cuuint32_t b[3] = {64, (cuuint32_t)brows, (cuuint32_t)bch};
    return make_map(enc, p, d, s, b);
}

CUtensorMap map_groups(EncodeFn enc, const void* p, int rows, int cols, int grp, int bg, int bch) {
    CUtensorMap m;
    cuuint64_t d[4] = {64, (cuuint64_t)grp, (cuuint64_t)(rows / grp), (cuuint64_t)(cols / 64)};
    cuuint64_t s[3] = {(cuuint64_t)cols * 2, (cuuint64_t)cols * 2 * grp, 128};
    cuuint32_t b[4] = {64, 8, (cuuint32_t)bg, (cuuint32_t)bch}, es[4] = {1, 1, 1, 1};
    enc(&m, CU_TENSOR_MAP_DATA_TYPE_BFLOAT16, 4, const_cast<void*>(p), d, s, b, es, CU_TENSOR_MAP_INTERLEAVE_NONE,
        CU_TENSOR_MAP_SWIZZLE_128B, CU_TENSOR_MAP_L2_PROMOTION_L2_128B, CU_TENSOR_MAP_FLOAT_OOB_FILL_NONE);
    return m;
}

__global__ void topo_probe() {}

void build_buckets(unsigned char* bucket) {
    for (int i = 0; i < 72; i++) bucket[i] = (unsigned char)((i >> 2) > 15 ? 15 : (i >> 2));
    int n[9] = {0};
    cudaFuncSetAttribute(topo_probe, cudaFuncAttributeMaxDynamicSharedMemorySize, SMEM_BYTES);
    cudaFuncSetAttribute(topo_probe, cudaFuncAttributeNonPortableClusterSizeAllowed, 1);
    for (int k = 1; k <= 8; k++) {
        cudaLaunchConfig_t cfg = {};
        cfg.gridDim = dim3(2 * k * 8); cfg.blockDim = dim3(32); cfg.dynamicSmemBytes = SMEM_BYTES;
        cudaLaunchAttribute at[1];
        at[0].id = cudaLaunchAttributeClusterDimension;
        at[0].val.clusterDim.x = 2 * k; at[0].val.clusterDim.y = 1; at[0].val.clusterDim.z = 1;
        cfg.attrs = at; cfg.numAttrs = 1;
        if (cudaOccupancyMaxActiveClusters(&n[k], topo_probe, &cfg) != cudaSuccess) { cudaGetLastError(); return; }
    }
    int cnt[10], best[10], found = 0;
    for (long code = 0; code < 387420489L && !found; code++) {
        long v = code; int g = 0, tot = 0;
        for (int t = 9; t >= 1; t--) { cnt[t] = (int)(v % 9); v /= 9; g += cnt[t]; tot += cnt[t] * t; }
        if (g > 8) {
            long p = 1; while ((code / p) % 9 == 0) p *= 9;
            code += (9 - (code / p) % 9) * p - 1;
            continue;
        }
        if (tot != n[1]) continue;
        int a2 = 0, a4 = 0, a8 = 0, a5 = 0, a6 = 0, a7 = 0;
        for (int t = 1; t <= 9; t++) { a2 += cnt[t] * (t / 2); a4 += cnt[t] * (t / 4); a8 += cnt[t] * (t / 8); a5 += cnt[t] * (t / 5); a6 += cnt[t] * (t / 6); a7 += cnt[t] * (t / 7); }
        if (a2 == n[2] && a4 == n[4] && a8 == n[8] && a5 == n[5] && a6 == n[6] && a7 == n[7]) { found = 1; for (int t = 1; t <= 9; t++) best[t] = cnt[t]; }
    }
    if (!found || n[1] > 72) return;
    int width[9], start[10];
    start[0] = 0;
    for (int r = 0; r < 9; r++) { width[r] = 0; for (int t = r + 1; t <= 9; t++) width[r] += best[t]; start[r + 1] = start[r] + width[r]; }
    int grp[72][4], gsz[72], ng = 0;
    for (int r0 = 0; r0 < 9 && width[r0] > 0;) {
        int r1 = r0;
        while (r1 < 9 && width[r1] == width[r0]) r1++;
        for (int rr = r0; rr < r1; rr += 4)
            for (int j = 0; j < width[r0]; j++) {
                gsz[ng] = 0;
                for (int r = rr; r < r1 && r < rr + 4; r++) grp[ng][gsz[ng]++] = start[r] + j;
                ng++;
            }
        r0 = r1;
    }
    int fill[16] = {0};
    for (int sz = 4; sz >= 1; sz--)
        for (int g = 0; g < ng; g++) {
            if (gsz[g] != sz) continue;
            int b = 0;
            while (b < 16 && fill[b] + sz > 4) b++;
            for (int i = 0; i < sz; i++) {
                int bb = b;
                if (bb == 16) { bb = 0; while (bb < 15 && fill[bb] >= 4) bb++; }
                bucket[grp[g][i]] = (unsigned char)bb;
                fill[bb]++;
            }
        }
}

}

extern "C" void kernel_launch(void* const* d_in, const int* in_sizes, int n_in, void* d_out, int out_size) {
    (void)in_sizes; (void)n_in; (void)out_size;
    static EncodeFn enc = nullptr;
    static void *p_h, *p_o, *p_ut, *p_wo, *p_kv, *p_gate, *p_flags, *p_tl, *p_llkv, *p_llo, *p_epoch;
    static unsigned char bucket[72];
    if (!enc) {
        build_buckets(bucket);
        void* fn = nullptr;
        cudaDriverEntryPointQueryResult qr;
        cudaGetDriverEntryPoint("cuTensorMapEncodeTiled", &fn, cudaEnableDefault, &qr);
        enc = (EncodeFn)fn;
        cudaFuncSetAttribute(fused_kernel, cudaFuncAttributeMaxDynamicSharedMemorySize, SMEM_BYTES);
        cudaGetSymbolAddress(&p_h, g_h);
        cudaGetSymbolAddress(&p_o, g_o);
        cudaGetSymbolAddress(&p_ut, g_ut);
        cudaGetSymbolAddress(&p_wo, g_wo);
        cudaGetSymbolAddress(&p_kv, g_kv);
        cudaGetSymbolAddress(&p_gate, g_gate);
        cudaGetSymbolAddress(&p_flags, g_flags);
        cudaGetSymbolAddress(&p_llkv, g_llkv);
        cudaGetSymbolAddress(&p_llo, g_llo);
        cudaGetSymbolAddress(&p_epoch, g_epoch);
    }
    Params P;
    P.x = (const __nv_bfloat16*)d_in[0];
    P.wqkv = (const __nv_bfloat16*)d_in[1];
    P.wo = (const __nv_bfloat16*)d_in[2];
    P.w1 = (const __nv_bfloat16*)d_in[4];
    P.b1 = (const __nv_bfloat16*)d_in[5];
    P.w2 = (const __nv_bfloat16*)d_in[6];
    P.b2 = (const __nv_bfloat16*)d_in[7];
    P.gw = (const __nv_bfloat16*)d_in[8];
    P.out = (__nv_bfloat16*)d_out;
    P.h = (__nv_bfloat16*)p_h;
    P.ut = (__nv_bfloat16*)p_ut;
    P.wos = (__nv_bfloat16*)p_wo;
    P.kv = (unsigned char*)p_kv;
    P.gate = (float*)p_gate;
    P.flags = (unsigned*)p_flags;
    P.llkv = (unsigned char*)p_llkv;
    P.llo = (unsigned char*)p_llo;
    P.epoch = (unsigned*)p_epoch;
    P.tl = (long long*)p_tl;
    for (int i = 0; i < 72; i++) P.bucket[i] = bucket[i];

    CUtensorMap tm_x = map_chunks(enc, P.x, S_LEN, D_DIM, 128, 1);
    CUtensorMap tm_wqkv;
    {
        cuuint64_t d[3] = {512, 512, 3}, s[2] = {3072, 1024};
        cuuint32_t b[3] = {64, 64, 3};
        tm_wqkv = make_map(enc, P.wqkv, d, s, b);
    }
    CUtensorMap tm_w1 = map_groups(enc, P.w1, S_LEN, F_DIM, 8, 8, 2);
    CUtensorMap tm_h = map_groups(enc, p_h, 2 * S_LEN, D_DIM, 8, 8, 2);
    CUtensorMap tm_w2 = map_groups(enc, P.w2, F_DIM, S_LEN, 16, 8, 2);
    CUtensorMap tm_ut = map_groups(enc, p_ut, 2 * F_DIM, D_DIM, 16, 8, 2);
    CUtensorMap tm_o = map_groups(enc, p_o, D_DIM, S_LEN, 8, 8, 2);
    CUtensorMap tm_ost = map_chunks(enc, p_o, D_DIM, S_LEN, 16, 1);
    CUtensorMap tm_ust = map_groups(enc, p_ut, 2 * F_DIM, D_DIM, 16, 4, 2);
    CUtensorMap tm_w1k = map_groups(enc, P.w1, S_LEN, F_DIM, 8, 8, 1);
    CUtensorMap tm_wo = map_groups(enc, p_wo, D_DIM, D_DIM, 8, 8, 2);

    fused_kernel<<<NCTA, 512, SMEM_BYTES>>>(P, tm_x, tm_wqkv, tm_w1, tm_h, tm_w2, tm_ut, tm_o, tm_wo, tm_ost, tm_ust, tm_w1k);
}
```
